```python
import torch

def _softmax(x, axis=-1):
    return torch.softmax(x, dim=axis)

def _gelu(x):
    return torch.nn.functional.gelu(x, approximate='tanh')

def _silu(x):
    return torch.nn.functional.silu(x)

def _sigmoid(x):
    return torch.sigmoid(x)

def _layernorm(x, axis=-1, eps=1e-05):
    m = x.mean(dim=axis, keepdim=True)
    v = x.var(dim=axis, keepdim=True, unbiased=False)
    return (x - m) / torch.sqrt(v + eps)

def _scatter_add(tgt, idx, src, axis=0):
    return tgt.clone().index_add_(axis, idx, src)

def _segment_sum(src, seg, n):
    out = torch.zeros((n,) + src.shape[1:], dtype=src.dtype)
    return out.index_add_(0, seg, src)

def _pad(x, pw):
    flat = tuple((v for pair in reversed(pw) for v in pair))
    return torch.nn.functional.pad(x, flat)
kernel_name = 'adaLN_cond__sliding_block_cached__mixer_s_mlp__prompt'

def setup_inputs():

    _w = lambda a: (lambda t: t.to(torch.bfloat16) if t.is_floating_point() else t)(torch.as_tensor(a))

    def _A_setup():
        B, Sq, D = (1, 2048, 448)
        Hq, Hkv, Sk, Dh = (16, 8, 2048, 256)
        assert Hq % Hkv == 0, (Hq, Hkv)
        return {'x': _w((lambda *s: torch.randn(*s, dtype=torch.bfloat16) * 0.1)(B, Sq, D)), 'k_cache': _w((lambda *s: torch.randn(*s, dtype=torch.bfloat16) * 0.8)(B, Hkv, Sk, Dh)), 'v_cache': _w((lambda *s: torch.randn(*s, dtype=torch.bfloat16) * 0.8)(B, Hkv, Sk, Dh)), 'wq': _w((lambda *s: torch.randn(*s, dtype=torch.bfloat16) * 0.8)(D, Hq * Dh) * D ** (-0.5)), 'wo': _w((lambda *s: torch.randn(*s, dtype=torch.bfloat16) * 0.8)(Hq * Dh, D) * (Hq * Dh) ** (-0.5))}
    _A_in = _A_setup()

    def _B_setup():
        B, S, D, F = (1, 2048, 448, 1792)
        return {'x': _w((lambda *s: torch.randn(*s, dtype=torch.bfloat16) * 0.1)(B, S, D)), 'w1': _w((lambda *s: torch.randn(*s, dtype=torch.bfloat16) * 3.2)(D, D) * D ** (-0.5)), 'w2': _w((lambda *s: torch.randn(*s, dtype=torch.bfloat16) * 3.2)(D, D) * D ** (-0.5)), 'w3': _w((lambda *s: torch.randn(*s, dtype=torch.bfloat16) * 3.2)(D, F) * D ** (-0.5)), 'w4': _w((lambda *s: torch.randn(*s, dtype=torch.bfloat16) * 3.2)(F, D) * F ** (-0.5))}
    _B_in = _B_setup()
    return {'A_x': _A_in['x'], 'A_k_cache': _A_in['k_cache'], 'A_v_cache': _A_in['v_cache'], 'A_wq': _A_in['wq'], 'A_wo': _A_in['wo'], 'B_x': _B_in['x'], 'B_w1': _B_in['w1'], 'B_w2': _B_in['w2'], 'B_w3': _B_in['w3'], 'B_w4': _B_in['w4'], 'c': _w((lambda *s: torch.randn(*s, dtype=torch.bfloat16) * 0.2)(1, 448) * 8.0), 'w_mod': _w((lambda *s: torch.randn(*s, dtype=torch.bfloat16) * 0.2)(448, 6 * 448) * 448 ** (-0.5) * 8.0)}

def reference(A_x, A_k_cache, A_v_cache, A_wq, A_wo, B_x, B_w1, B_w2, B_w3, B_w4, c, w_mod):

    def _A_ref(x, k_cache, v_cache, wq, wo):
        B, Sq, D = x.shape
        Hq, Dh = (16, 256)
        Hkv, Sk = (k_cache.shape[1], k_cache.shape[2])
        W = min(4096, max(256, Sk // 4))
        rep = Hq // Hkv
        q = (lambda x, *d: x.permute(*d))((x @ wq).reshape(B, Sq, Hq, Dh), 0, 2, 1, 3)
        k = (lambda x, n, axis: torch.repeat_interleave(x, n, dim=axis))(k_cache[:, :, Sk - W:, :], rep, axis=1)
        v = (lambda x, n, axis: torch.repeat_interleave(x, n, dim=axis))(v_cache[:, :, Sk - W:, :], rep, axis=1)
        scores = torch.einsum('bhqd,bhkd->bhqk', q, k) * Dh ** (-0.5)
        p = _softmax(scores, axis=-1)
        o = torch.einsum('bhqk,bhkd->bhqd', p, v)
        return (lambda x, *d: x.permute(*d))(o, 0, 2, 1, 3).reshape(B, Sq, Hq * Dh) @ wo

    def _B_ref(x, w1, w2, w3, w4):
        B, S, D = x.shape
        h = _gelu(_layernorm(x, axis=-1) @ w1)
        c = D // 4
        g0 = _pad(h[:, :, 0 * c:1 * c], ((0, 0), (1, 0), (0, 0)))[:, :S, :]
        g1 = _pad(h[:, :, 1 * c:2 * c], ((0, 0), (0, 1), (0, 0)))[:, 1:, :]
        g2 = _pad(h[:, :, 2 * c:3 * c], ((0, 0), (2, 0), (0, 0)))[:, :S, :]
        g3 = _pad(h[:, :, 3 * c:], ((0, 0), (0, 2), (0, 0)))[:, 2:, :]
        hs = torch.concatenate([g0, g1, g2, g3], axis=-1) @ w2
        x1 = x + hs
        h2 = _gelu(_layernorm(x1, axis=-1) @ w3) @ w4
        return x1 + h2
    x = A_x
    mod = (_silu(c) @ w_mod).reshape(c.shape[0], 6, 1, -1)
    sa, ca, ga, sb, cb, gb = (mod[:, 0].clone(), mod[:, 1].clone(), mod[:, 2].clone(), mod[:, 3].clone(), mod[:, 4].clone(), mod[:, 5].clone())
    h = _layernorm(x, axis=-1) * (1 + ca) + sa
    x = x + ga * _A_ref(h, A_k_cache, A_v_cache, A_wq, A_wo)
    h = _layernorm(x, axis=-1) * (1 + cb) + sb
    x = x + gb * _B_ref(h, B_w1, B_w2, B_w3, B_w4)
    return x
```

```cpp
#include <cuda_runtime.h>
#include <cuda.h>
#include <cuda_bf16.h>
#include <stdint.h>

namespace {

constexpr int SEQ = 2048;
constexpr int DM = 448;
constexpr int HKV = 8;
constexpr int DH = 256;
constexpr int SKV = 2048;
constexpr int WIN = 512;
constexpr int FF = 1792;
constexpr float LN_EPS = 1e-5f;
constexpr int NMAIN = 128, NHELP = 4, NCTA = NMAIN + NHELP;

struct SyncState {
  unsigned epoch; unsigned pad0[31];
  unsigned done;  unsigned pad1[31];
  unsigned init;  unsigned pad2[31];
  unsigned xi[32 * 8];
  unsigned x1a[16 * 8];
  unsigned x1b[16 * 8];
  unsigned x1[16 * 8];
  unsigned ts[32 * 8];
  unsigned base[32 * 8];
  unsigned y1[32 * 8];
};
__device__ SyncState g_sync;
__device__ uint2 g_modt[6 * DM];
__device__ __align__(1024) __nv_bfloat16 g_x1[SEQ * DM];
__device__ __align__(1024) __nv_bfloat16 g_w1x[4 * DM * 128];
__device__ __align__(128) float g_s1v[4 * 3072];
__device__ __align__(1024) __nv_bfloat16 g_w3x[16 * FF];
__device__ __align__(1024) __nv_bfloat16 g_ts[(SEQ + 4) * DM];
__device__ __align__(1024) __nv_bfloat16 g_y1[SEQ * DM];
__device__ __align__(128) float g_ystat[8 * SEQ * 2];

__device__ __forceinline__ uint32_t smem_u32(const void* p) { return (uint32_t)__cvta_generic_to_shared(p); }
__device__ __forceinline__ void mbar_init(uint32_t bar, uint32_t cnt) {
  asm volatile("mbarrier.init.shared::cta.b64 [%0], %1;" ::"r"(bar), "r"(cnt));
}
__device__ __forceinline__ void mbar_expect_tx(uint32_t bar, uint32_t bytes) {
  asm volatile("mbarrier.arrive.expect_tx.shared::cta.b64 _, [%0], %1;" ::"r"(bar), "r"(bytes) : "memory");
}
__device__ __forceinline__ void mbar_arrive(uint32_t bar) {
  asm volatile("mbarrier.arrive.shared::cta.b64 _, [%0];" ::"r"(bar) : "memory");
}
__device__ unsigned g_fail[8];
__device__ __forceinline__ void mbar_wait(uint32_t bar, uint32_t parity) {
  asm volatile(
      "{\n.reg .pred p;\n"
      "WAIT_%=:\n"
      "mbarrier.try_wait.parity.shared::cta.b64 p, [%0], %1;\n"
      "@!p bra WAIT_%=;\n}" ::"r"(bar), "r"(parity) : "memory");
}
__device__ __forceinline__ void tma_load_2d(uint32_t dst, const CUtensorMap* m, int c0, int c1, uint32_t bar) {
  asm volatile("cp.async.bulk.tensor.2d.shared::cluster.global.mbarrier::complete_tx::bytes [%0], [%1, {%3, %4}], [%2];"
               ::"r"(dst), "l"(m), "r"(bar), "r"(c0), "r"(c1) : "memory");
}
__device__ __forceinline__ void tma_load_3d(uint32_t dst, const CUtensorMap* m, int c0, int c1, int c2, uint32_t bar) {
  asm volatile("cp.async.bulk.tensor.3d.shared::cluster.global.mbarrier::complete_tx::bytes [%0], [%1, {%3, %4, %5}], [%2];"
               ::"r"(dst), "l"(m), "r"(bar), "r"(c0), "r"(c1), "r"(c2) : "memory");
}
__device__ __forceinline__ void tma_store_2d(const CUtensorMap* m, uint32_t src, int c0, int c1) {
  asm volatile("cp.async.bulk.tensor.2d.global.shared::cta.bulk_group [%0, {%2, %3}], [%1];"
               ::"l"(m), "r"(src), "r"(c0), "r"(c1) : "memory");
}
__device__ __forceinline__ void tma_red_2d(const CUtensorMap* m, uint32_t src, int c0, int c1) {
  asm volatile("cp.reduce.async.bulk.tensor.2d.global.shared::cta.add.tile.bulk_group [%0, {%2, %3}], [%1];"
               ::"l"(m), "r"(src), "r"(c0), "r"(c1) : "memory");
}
__device__ __forceinline__ void bulk_store_1d(void* dst, uint32_t src, uint32_t bytes) {
  asm volatile("cp.async.bulk.global.shared::cta.bulk_group [%0], [%1], %2;" ::"l"(dst), "r"(src), "r"(bytes) : "memory");
}
__device__ __forceinline__ void bulk_load_1d(uint32_t dst, const void* src, uint32_t bytes, uint32_t bar) {
  asm volatile("cp.async.bulk.shared::cluster.global.mbarrier::complete_tx::bytes [%0], [%1], %2, [%3];" ::"r"(dst), "l"(src), "r"(bytes), "r"(bar) : "memory");
}
__device__ __forceinline__ void bulk_commit() { asm volatile("cp.async.bulk.commit_group;" ::: "memory"); }
template <int N> __device__ __forceinline__ void bulk_wait_read() { asm volatile("cp.async.bulk.wait_group.read %0;" ::"n"(N) : "memory"); }
template <int N> __device__ __forceinline__ void bulk_wait() { asm volatile("cp.async.bulk.wait_group %0;" ::"n"(N) : "memory"); }
__device__ __forceinline__ void fence_async_smem() { asm volatile("fence.proxy.async.shared::cta;" ::: "memory"); }
__device__ __forceinline__ void fence_async_all() { asm volatile("fence.proxy.async.global;" ::: "memory"); }
__device__ __forceinline__ void named_bar_sync(int id, int n) { __syncwarp(); asm volatile("bar.sync %0, %1;" ::"r"(id), "r"(n) : "memory"); }
__device__ __forceinline__ void named_bar_arrive(int id, int n) { __syncwarp(); asm volatile("bar.arrive %0, %1;" ::"r"(id), "r"(n) : "memory"); }
__device__ __forceinline__ void wg_fence() { asm volatile("wgmma.fence.sync.aligned;" ::: "memory"); }
__device__ __forceinline__ void wg_commit() { asm volatile("wgmma.commit_group.sync.aligned;" ::: "memory"); }
template <int N> __device__ __forceinline__ void wg_wait() { asm volatile("wgmma.wait_group.sync.aligned %0;" ::"n"(N) : "memory"); }
template <int N> __device__ __forceinline__ void reg_alloc() { asm volatile("setmaxnreg.inc.sync.aligned.u32 %0;" ::"n"(N)); }
template <int N> __device__ __forceinline__ void reg_dealloc() { asm volatile("setmaxnreg.dec.sync.aligned.u32 %0;" ::"n"(N)); }
__device__ __forceinline__ void ldsm_x4(uint32_t addr, uint32_t& r0, uint32_t& r1, uint32_t& r2, uint32_t& r3) {
  asm volatile("ldmatrix.sync.aligned.m8n8.x4.shared.b16 {%0, %1, %2, %3}, [%4];"
               : "=r"(r0), "=r"(r1), "=r"(r2), "=r"(r3) : "r"(addr) : "memory");
}
__device__ __forceinline__ void stsm_x4(uint32_t addr, uint32_t r0, uint32_t r1, uint32_t r2, uint32_t r3) {
  asm volatile("stmatrix.sync.aligned.m8n8.x4.shared.b16 [%0], {%1, %2, %3, %4};"
               ::"r"(addr), "r"(r0), "r"(r1), "r"(r2), "r"(r3));
}
__device__ __forceinline__ uint32_t pack_bf16(float lo, float hi) {
  uint32_t r;
  asm("cvt.rn.bf16x2.f32 %0, %1, %2;" : "=r"(r) : "f"(hi), "f"(lo));
  return r;
}
__device__ __forceinline__ float bf_lo(uint32_t v) { return __uint_as_float(v << 16); }
__device__ __forceinline__ float bf_hi(uint32_t v) { return __uint_as_float(v & 0xffff0000u); }
__device__ __forceinline__ float bf_lo_p(uint32_t v) { uint32_t r; asm volatile("prmt.b32 %0, %1, 0, 0x1044;" : "=r"(r) : "r"(v)); return __uint_as_float(r); }
__device__ __forceinline__ float bf_hi_p(uint32_t v) { uint32_t r; asm volatile("prmt.b32 %0, %1, 0, 0x3244;" : "=r"(r) : "r"(v)); return __uint_as_float(r); }
__device__ __forceinline__ float bf_round(float x) { return bf_lo(pack_bf16(x, 0.f) & 0xffffu); }
__device__ __forceinline__ float ex2(float x) { float y; asm("ex2.approx.ftz.f32 %0, %1;" : "=f"(y) : "f"(x)); return y; }
__device__ __forceinline__ float rcp_approx(float x) { float y; asm("rcp.approx.ftz.f32 %0, %1;" : "=f"(y) : "f"(x)); return y; }
__device__ __forceinline__ float tanh_approx(float x) { float y; asm("tanh.approx.f32 %0, %1;" : "=f"(y) : "f"(x)); return y; }
__device__ __forceinline__ float gelu2(float x) {
  const float u = x * fmaf(x * x, 0.7978845608028654f * 0.044715f, 0.7978845608028654f);
  return fmaf(x, tanh_approx(u), x);
}
__device__ __forceinline__ float4 lds_f4(uint32_t a) { float4 v; asm volatile("ld.shared.v4.f32 {%0,%1,%2,%3}, [%4];" : "=f"(v.x), "=f"(v.y), "=f"(v.z), "=f"(v.w) : "r"(a)); return v; }
__device__ __forceinline__ float2 lds_f2(uint32_t a) { float2 v; asm volatile("ld.shared.v2.f32 {%0,%1}, [%2];" : "=f"(v.x), "=f"(v.y) : "r"(a)); return v; }
__device__ __forceinline__ float2 ldc_f2(uint32_t a) { float2 v; asm("ld.shared.v2.f32 {%0,%1}, [%2];" : "=f"(v.x), "=f"(v.y) : "r"(a)); return v; }
__device__ __forceinline__ float4 ldc_f4(uint32_t a) { float4 v; asm("ld.shared.v4.f32 {%0,%1,%2,%3}, [%4];" : "=f"(v.x), "=f"(v.y), "=f"(v.z), "=f"(v.w) : "r"(a)); return v; }
__device__ __forceinline__ float ldc_f1(uint32_t a) { float v; asm("ld.shared.f32 %0, [%1];" : "=f"(v) : "r"(a)); return v; }
__device__ __forceinline__ uint32_t ldc_u1(uint32_t a) { uint32_t v; asm("ld.shared.u32 %0, [%1];" : "=r"(v) : "r"(a)); return v; }
__device__ __forceinline__ float lds_f1(uint32_t a) { float v; asm volatile("ld.shared.f32 %0, [%1];" : "=f"(v) : "r"(a)); return v; }
__device__ __forceinline__ uint32_t lds_u1(uint32_t a) { uint32_t v; asm volatile("ld.shared.u32 %0, [%1];" : "=r"(v) : "r"(a)); return v; }
__device__ __forceinline__ void sts_f1(uint32_t a, float v) { asm volatile("st.shared.f32 [%0], %1;" ::"r"(a), "f"(v) : "memory"); }
__device__ __forceinline__ void sts_b16(uint32_t a, uint32_t v) { asm volatile("st.shared.b16 [%0], %1;" ::"r"(a), "h"((unsigned short)v) : "memory"); }
__device__ __forceinline__ uint2 ldc_u2(uint32_t a) { uint2 v; asm("ld.shared.v2.u32 {%0,%1}, [%2];" : "=r"(v.x), "=r"(v.y) : "r"(a)); return v; }
__device__ __forceinline__ uint4 ldc_u4(uint32_t a) { uint4 v; asm("ld.shared.v4.u32 {%0,%1,%2,%3}, [%4];" : "=r"(v.x), "=r"(v.y), "=r"(v.z), "=r"(v.w) : "r"(a)); return v; }
__device__ __forceinline__ uint32_t hfma2_bf16(uint32_t a, uint32_t b, uint32_t c) { uint32_t r; asm("fma.rn.bf16x2 %0, %1, %2, %3;" : "=r"(r) : "r"(a), "r"(b), "r"(c)); return r; }
__device__ __forceinline__ uint32_t hmul2_bf16(uint32_t a, uint32_t b) { uint32_t r; asm("mul.rn.bf16x2 %0, %1, %2;" : "=r"(r) : "r"(a), "r"(b)); return r; }
__device__ __forceinline__ void sts_f2(uint32_t a, float x, float y) { asm volatile("st.shared.v2.f32 [%0], {%1, %2};" ::"r"(a), "f"(x), "f"(y) : "memory"); }
template <int N> __device__ __forceinline__ void fence_regs(float (&d)[N]) {
#pragma unroll
  for (int i = 0; i < N; i++) asm volatile("" : "+f"(d[i])::"memory");
}
template <int N> __device__ __forceinline__ void fence_regs_u(uint32_t (&d)[N]) {
#pragma unroll
  for (int i = 0; i < N; i++) asm volatile("" : "+r"(d[i])::"memory");
}
__device__ __forceinline__ uint64_t make_desc(uint32_t addr, uint32_t lbo_bytes, uint32_t sbo_bytes) {
  uint64_t d = 0;
  d |= (uint64_t)((addr & 0x3FFFF) >> 4);
  d |= (uint64_t)(lbo_bytes >> 4) << 16;
  d |= (uint64_t)(sbo_bytes >> 4) << 32;
  d |= (uint64_t)1 << 62;
  return d;
}
#define DBG_FAIL(k)
#define POLL_NS 0
__device__ __forceinline__ void flag_arrive(unsigned* f) { asm volatile("red.release.gpu.global.add.u32 [%0], 1;" ::"l"(f) : "memory"); }
__device__ __forceinline__ void flag_arrive_release(unsigned* f) { asm volatile("fence.proxy.async.global;\n\tred.release.gpu.global.add.u32 [%0], 1;" ::"l"(f) : "memory"); }
__device__ __forceinline__ void flag_arrive_stored(unsigned* f) { asm volatile("red.relaxed.gpu.global.add.u32 [%0], 1;" ::"l"(f) : "memory"); }
__device__ __forceinline__ void flag_wait(const unsigned* f, unsigned target) {
  unsigned v;
#pragma unroll 1
  for (int guard = 0; guard < (1 << 20); guard++) {
    asm volatile("ld.acquire.gpu.global.u32 %0, [%1];" : "=r"(v) : "l"(f) : "memory");
    if ((int)(v - target) >= 0) break;
  }
}
__device__ __forceinline__ float mod_wait(int i, unsigned tag) {
  unsigned long long w;
#pragma unroll 1
  for (int guard = 0; guard < (1 << 18); guard++) {
    asm volatile("ld.relaxed.gpu.global.b64 %0, [%1];" : "=l"(w) : "l"(&g_modt[i]) : "memory");
    if ((unsigned)(w >> 32) == tag) break;
  }
  return __uint_as_float((unsigned)w);
}

#define PROF(i)
#define PROFA(i) PROF(i)
#define PROFB(i)
#define PROFC(i)
template <int TB> __device__ __forceinline__ void wgmma_rs_n128(float (&d)[64], uint32_t a0, uint32_t a1, uint32_t a2, uint32_t a3, uint64_t db, int sc) {
  asm volatile("{\n.reg .pred p;\nsetp.ne.b32 p, %69, 0;\n"
    "wgmma.mma_async.sync.aligned.m64n128k16.f32.bf16.bf16 {%0, %1, %2, %3, %4, %5, %6, %7, %8, %9, %10, %11, %12, %13, %14, %15, %16, %17, %18, %19, %20, %21, %22, %23, %24, %25, %26, %27, %28, %29, %30, %31, %32, %33, %34, %35, %36, %37, %38, %39, %40, %41, %42, %43, %44, %45, %46, %47, %48, %49, %50, %51, %52, %53, %54, %55, %56, %57, %58, %59, %60, %61, %62, %63}, {%64, %65, %66, %67}, %68, p, 1, 1, %70;\n}\n"
    : "+f"(d[0]), "+f"(d[1]), "+f"(d[2]), "+f"(d[3]), "+f"(d[4]), "+f"(d[5]), "+f"(d[6]), "+f"(d[7]), "+f"(d[8]), "+f"(d[9]), "+f"(d[10]), "+f"(d[11]), "+f"(d[12]), "+f"(d[13]), "+f"(d[14]), "+f"(d[15]), "+f"(d[16]), "+f"(d[17]), "+f"(d[18]), "+f"(d[19]), "+f"(d[20]), "+f"(d[21]), "+f"(d[22]), "+f"(d[23]), "+f"(d[24]), "+f"(d[25]), "+f"(d[26]), "+f"(d[27]), "+f"(d[28]), "+f"(d[29]), "+f"(d[30]), "+f"(d[31]), "+f"(d[32]), "+f"(d[33]), "+f"(d[34]), "+f"(d[35]), "+f"(d[36]), "+f"(d[37]), "+f"(d[38]), "+f"(d[39]), "+f"(d[40]), "+f"(d[41]), "+f"(d[42]), "+f"(d[43]), "+f"(d[44]), "+f"(d[45]), "+f"(d[46]), "+f"(d[47]), "+f"(d[48]), "+f"(d[49]), "+f"(d[50]), "+f"(d[51]), "+f"(d[52]), "+f"(d[53]), "+f"(d[54]), "+f"(d[55]), "+f"(d[56]), "+f"(d[57]), "+f"(d[58]), "+f"(d[59]), "+f"(d[60]), "+f"(d[61]), "+f"(d[62]), "+f"(d[63])
    : "r"(a0), "r"(a1), "r"(a2), "r"(a3), "l"(db), "r"(sc), "n"(TB));
}
template <int TB> __device__ __forceinline__ void wgmma_ss_n128(float (&d)[64], uint64_t da, uint64_t db, int sc) {
  asm volatile("{\n.reg .pred p;\nsetp.ne.b32 p, %66, 0;\n"
    "wgmma.mma_async.sync.aligned.m64n128k16.f32.bf16.bf16 {%0, %1, %2, %3, %4, %5, %6, %7, %8, %9, %10, %11, %12, %13, %14, %15, %16, %17, %18, %19, %20, %21, %22, %23, %24, %25, %26, %27, %28, %29, %30, %31, %32, %33, %34, %35, %36, %37, %38, %39, %40, %41, %42, %43, %44, %45, %46, %47, %48, %49, %50, %51, %52, %53, %54, %55, %56, %57, %58, %59, %60, %61, %62, %63}, %64, %65, p, 1, 1, 0, %67;\n}\n"
    : "+f"(d[0]), "+f"(d[1]), "+f"(d[2]), "+f"(d[3]), "+f"(d[4]), "+f"(d[5]), "+f"(d[6]), "+f"(d[7]), "+f"(d[8]), "+f"(d[9]), "+f"(d[10]), "+f"(d[11]), "+f"(d[12]), "+f"(d[13]), "+f"(d[14]), "+f"(d[15]), "+f"(d[16]), "+f"(d[17]), "+f"(d[18]), "+f"(d[19]), "+f"(d[20]), "+f"(d[21]), "+f"(d[22]), "+f"(d[23]), "+f"(d[24]), "+f"(d[25]), "+f"(d[26]), "+f"(d[27]), "+f"(d[28]), "+f"(d[29]), "+f"(d[30]), "+f"(d[31]), "+f"(d[32]), "+f"(d[33]), "+f"(d[34]), "+f"(d[35]), "+f"(d[36]), "+f"(d[37]), "+f"(d[38]), "+f"(d[39]), "+f"(d[40]), "+f"(d[41]), "+f"(d[42]), "+f"(d[43]), "+f"(d[44]), "+f"(d[45]), "+f"(d[46]), "+f"(d[47]), "+f"(d[48]), "+f"(d[49]), "+f"(d[50]), "+f"(d[51]), "+f"(d[52]), "+f"(d[53]), "+f"(d[54]), "+f"(d[55]), "+f"(d[56]), "+f"(d[57]), "+f"(d[58]), "+f"(d[59]), "+f"(d[60]), "+f"(d[61]), "+f"(d[62]), "+f"(d[63])
    : "l"(da), "l"(db), "r"(sc), "n"(TB));
}
template <int TB> __device__ __forceinline__ void wgmma_rs_n256(float (&d)[128], uint32_t a0, uint32_t a1, uint32_t a2, uint32_t a3, uint64_t db, int sc) {
  asm volatile("{\n.reg .pred p;\nsetp.ne.b32 p, %133, 0;\n"
    "wgmma.mma_async.sync.aligned.m64n256k16.f32.bf16.bf16 {%0, %1, %2, %3, %4, %5, %6, %7, %8, %9, %10, %11, %12, %13, %14, %15, %16, %17, %18, %19, %20, %21, %22, %23, %24, %25, %26, %27, %28, %29, %30, %31, %32, %33, %34, %35, %36, %37, %38, %39, %40, %41, %42, %43, %44, %45, %46, %47, %48, %49, %50, %51, %52, %53, %54, %55, %56, %57, %58, %59, %60, %61, %62, %63, %64, %65, %66, %67, %68, %69, %70, %71, %72, %73, %74, %75, %76, %77, %78, %79, %80, %81, %82, %83, %84, %85, %86, %87, %88, %89, %90, %91, %92, %93, %94, %95, %96, %97, %98, %99, %100, %101, %102, %103, %104, %105, %106, %107, %108, %109, %110, %111, %112, %113, %114, %115, %116, %117, %118, %119, %120, %121, %122, %123, %124, %125, %126, %127}, {%128, %129, %130, %131}, %132, p, 1, 1, %134;\n}\n"
    : "+f"(d[0]), "+f"(d[1]), "+f"(d[2]), "+f"(d[3]), "+f"(d[4]), "+f"(d[5]), "+f"(d[6]), "+f"(d[7]), "+f"(d[8]), "+f"(d[9]), "+f"(d[10]), "+f"(d[11]), "+f"(d[12]), "+f"(d[13]), "+f"(d[14]), "+f"(d[15]), "+f"(d[16]), "+f"(d[17]), "+f"(d[18]), "+f"(d[19]), "+f"(d[20]), "+f"(d[21]), "+f"(d[22]), "+f"(d[23]), "+f"(d[24]), "+f"(d[25]), "+f"(d[26]), "+f"(d[27]), "+f"(d[28]), "+f"(d[29]), "+f"(d[30]), "+f"(d[31]), "+f"(d[32]), "+f"(d[33]), "+f"(d[34]), "+f"(d[35]), "+f"(d[36]), "+f"(d[37]), "+f"(d[38]), "+f"(d[39]), "+f"(d[40]), "+f"(d[41]), "+f"(d[42]), "+f"(d[43]), "+f"(d[44]), "+f"(d[45]), "+f"(d[46]), "+f"(d[47]), "+f"(d[48]), "+f"(d[49]), "+f"(d[50]), "+f"(d[51]), "+f"(d[52]), "+f"(d[53]), "+f"(d[54]), "+f"(d[55]), "+f"(d[56]), "+f"(d[57]), "+f"(d[58]), "+f"(d[59]), "+f"(d[60]), "+f"(d[61]), "+f"(d[62]), "+f"(d[63]), "+f"(d[64]), "+f"(d[65]), "+f"(d[66]), "+f"(d[67]), "+f"(d[68]), "+f"(d[69]), "+f"(d[70]), "+f"(d[71]), "+f"(d[72]), "+f"(d[73]), "+f"(d[74]), "+f"(d[75]), "+f"(d[76]), "+f"(d[77]), "+f"(d[78]), "+f"(d[79]), "+f"(d[80]), "+f"(d[81]), "+f"(d[82]), "+f"(d[83]), "+f"(d[84]), "+f"(d[85]), "+f"(d[86]), "+f"(d[87]), "+f"(d[88]), "+f"(d[89]), "+f"(d[90]), "+f"(d[91]), "+f"(d[92]), "+f"(d[93]), "+f"(d[94]), "+f"(d[95]), "+f"(d[96]), "+f"(d[97]), "+f"(d[98]), "+f"(d[99]), "+f"(d[100]), "+f"(d[101]), "+f"(d[102]), "+f"(d[103]), "+f"(d[104]), "+f"(d[105]), "+f"(d[106]), "+f"(d[107]), "+f"(d[108]), "+f"(d[109]), "+f"(d[110]), "+f"(d[111]), "+f"(d[112]), "+f"(d[113]), "+f"(d[114]), "+f"(d[115]), "+f"(d[116]), "+f"(d[117]), "+f"(d[118]), "+f"(d[119]), "+f"(d[120]), "+f"(d[121]), "+f"(d[122]), "+f"(d[123]), "+f"(d[124]), "+f"(d[125]), "+f"(d[126]), "+f"(d[127])
    : "r"(a0), "r"(a1), "r"(a2), "r"(a3), "l"(db), "r"(sc), "n"(TB));
}
template <int TB> __device__ __forceinline__ void wgmma_ss_n256(float (&d)[128], uint64_t da, uint64_t db, int sc) {
  asm volatile("{\n.reg .pred p;\nsetp.ne.b32 p, %130, 0;\n"
    "wgmma.mma_async.sync.aligned.m64n256k16.f32.bf16.bf16 {%0, %1, %2, %3, %4, %5, %6, %7, %8, %9, %10, %11, %12, %13, %14, %15, %16, %17, %18, %19, %20, %21, %22, %23, %24, %25, %26, %27, %28, %29, %30, %31, %32, %33, %34, %35, %36, %37, %38, %39, %40, %41, %42, %43, %44, %45, %46, %47, %48, %49, %50, %51, %52, %53, %54, %55, %56, %57, %58, %59, %60, %61, %62, %63, %64, %65, %66, %67, %68, %69, %70, %71, %72, %73, %74, %75, %76, %77, %78, %79, %80, %81, %82, %83, %84, %85, %86, %87, %88, %89, %90, %91, %92, %93, %94, %95, %96, %97, %98, %99, %100, %101, %102, %103, %104, %105, %106, %107, %108, %109, %110, %111, %112, %113, %114, %115, %116, %117, %118, %119, %120, %121, %122, %123, %124, %125, %126, %127}, %128, %129, p, 1, 1, 0, %131;\n}\n"
    : "+f"(d[0]), "+f"(d[1]), "+f"(d[2]), "+f"(d[3]), "+f"(d[4]), "+f"(d[5]), "+f"(d[6]), "+f"(d[7]), "+f"(d[8]), "+f"(d[9]), "+f"(d[10]), "+f"(d[11]), "+f"(d[12]), "+f"(d[13]), "+f"(d[14]), "+f"(d[15]), "+f"(d[16]), "+f"(d[17]), "+f"(d[18]), "+f"(d[19]), "+f"(d[20]), "+f"(d[21]), "+f"(d[22]), "+f"(d[23]), "+f"(d[24]), "+f"(d[25]), "+f"(d[26]), "+f"(d[27]), "+f"(d[28]), "+f"(d[29]), "+f"(d[30]), "+f"(d[31]), "+f"(d[32]), "+f"(d[33]), "+f"(d[34]), "+f"(d[35]), "+f"(d[36]), "+f"(d[37]), "+f"(d[38]), "+f"(d[39]), "+f"(d[40]), "+f"(d[41]), "+f"(d[42]), "+f"(d[43]), "+f"(d[44]), "+f"(d[45]), "+f"(d[46]), "+f"(d[47]), "+f"(d[48]), "+f"(d[49]), "+f"(d[50]), "+f"(d[51]), "+f"(d[52]), "+f"(d[53]), "+f"(d[54]), "+f"(d[55]), "+f"(d[56]), "+f"(d[57]), "+f"(d[58]), "+f"(d[59]), "+f"(d[60]), "+f"(d[61]), "+f"(d[62]), "+f"(d[63]), "+f"(d[64]), "+f"(d[65]), "+f"(d[66]), "+f"(d[67]), "+f"(d[68]), "+f"(d[69]), "+f"(d[70]), "+f"(d[71]), "+f"(d[72]), "+f"(d[73]), "+f"(d[74]), "+f"(d[75]), "+f"(d[76]), "+f"(d[77]), "+f"(d[78]), "+f"(d[79]), "+f"(d[80]), "+f"(d[81]), "+f"(d[82]), "+f"(d[83]), "+f"(d[84]), "+f"(d[85]), "+f"(d[86]), "+f"(d[87]), "+f"(d[88]), "+f"(d[89]), "+f"(d[90]), "+f"(d[91]), "+f"(d[92]), "+f"(d[93]), "+f"(d[94]), "+f"(d[95]), "+f"(d[96]), "+f"(d[97]), "+f"(d[98]), "+f"(d[99]), "+f"(d[100]), "+f"(d[101]), "+f"(d[102]), "+f"(d[103]), "+f"(d[104]), "+f"(d[105]), "+f"(d[106]), "+f"(d[107]), "+f"(d[108]), "+f"(d[109]), "+f"(d[110]), "+f"(d[111]), "+f"(d[112]), "+f"(d[113]), "+f"(d[114]), "+f"(d[115]), "+f"(d[116]), "+f"(d[117]), "+f"(d[118]), "+f"(d[119]), "+f"(d[120]), "+f"(d[121]), "+f"(d[122]), "+f"(d[123]), "+f"(d[124]), "+f"(d[125]), "+f"(d[126]), "+f"(d[127])
    : "l"(da), "l"(db), "r"(sc), "n"(TB));
}
template <int TB> __device__ __forceinline__ void wgmma_ss_n64(float (&d)[32], uint64_t da, uint64_t db, int sc) {
  asm volatile("{\n.reg .pred p;\nsetp.ne.b32 p, %34, 0;\n"
    "wgmma.mma_async.sync.aligned.m64n64k16.f32.bf16.bf16 {%0, %1, %2, %3, %4, %5, %6, %7, %8, %9, %10, %11, %12, %13, %14, %15, %16, %17, %18, %19, %20, %21, %22, %23, %24, %25, %26, %27, %28, %29, %30, %31}, %32, %33, p, 1, 1, 0, %35;\n}\n"
    : "+f"(d[0]), "+f"(d[1]), "+f"(d[2]), "+f"(d[3]), "+f"(d[4]), "+f"(d[5]), "+f"(d[6]), "+f"(d[7]), "+f"(d[8]), "+f"(d[9]), "+f"(d[10]), "+f"(d[11]), "+f"(d[12]), "+f"(d[13]), "+f"(d[14]), "+f"(d[15]), "+f"(d[16]), "+f"(d[17]), "+f"(d[18]), "+f"(d[19]), "+f"(d[20]), "+f"(d[21]), "+f"(d[22]), "+f"(d[23]), "+f"(d[24]), "+f"(d[25]), "+f"(d[26]), "+f"(d[27]), "+f"(d[28]), "+f"(d[29]), "+f"(d[30]), "+f"(d[31])
    : "l"(da), "l"(db), "r"(sc), "n"(TB));
}
template <int TB> __device__ __forceinline__ void wgmma_rs_n64(float (&d)[32], uint32_t a0, uint32_t a1, uint32_t a2, uint32_t a3, uint64_t db, int sc) {
  asm volatile("{\n.reg .pred p;\nsetp.ne.b32 p, %37, 0;\n"
    "wgmma.mma_async.sync.aligned.m64n64k16.f32.bf16.bf16 {%0, %1, %2, %3, %4, %5, %6, %7, %8, %9, %10, %11, %12, %13, %14, %15, %16, %17, %18, %19, %20, %21, %22, %23, %24, %25, %26, %27, %28, %29, %30, %31}, {%32, %33, %34, %35}, %36, p, 1, 1, %38;\n}\n"
    : "+f"(d[0]), "+f"(d[1]), "+f"(d[2]), "+f"(d[3]), "+f"(d[4]), "+f"(d[5]), "+f"(d[6]), "+f"(d[7]), "+f"(d[8]), "+f"(d[9]), "+f"(d[10]), "+f"(d[11]), "+f"(d[12]), "+f"(d[13]), "+f"(d[14]), "+f"(d[15]), "+f"(d[16]), "+f"(d[17]), "+f"(d[18]), "+f"(d[19]), "+f"(d[20]), "+f"(d[21]), "+f"(d[22]), "+f"(d[23]), "+f"(d[24]), "+f"(d[25]), "+f"(d[26]), "+f"(d[27]), "+f"(d[28]), "+f"(d[29]), "+f"(d[30]), "+f"(d[31])
    : "r"(a0), "r"(a1), "r"(a2), "r"(a3), "l"(db), "r"(sc), "n"(TB));
}
template <int TB> __device__ __forceinline__ void wgmma_rs_n112(float (&d)[56], uint32_t a0, uint32_t a1, uint32_t a2, uint32_t a3, uint64_t db, int sc) {
  asm volatile("{\n.reg .pred p;\nsetp.ne.b32 p, %61, 0;\n"
    "wgmma.mma_async.sync.aligned.m64n112k16.f32.bf16.bf16 {%0, %1, %2, %3, %4, %5, %6, %7, %8, %9, %10, %11, %12, %13, %14, %15, %16, %17, %18, %19, %20, %21, %22, %23, %24, %25, %26, %27, %28, %29, %30, %31, %32, %33, %34, %35, %36, %37, %38, %39, %40, %41, %42, %43, %44, %45, %46, %47, %48, %49, %50, %51, %52, %53, %54, %55}, {%56, %57, %58, %59}, %60, p, 1, 1, %62;\n}\n"
    : "+f"(d[0]), "+f"(d[1]), "+f"(d[2]), "+f"(d[3]), "+f"(d[4]), "+f"(d[5]), "+f"(d[6]), "+f"(d[7]), "+f"(d[8]), "+f"(d[9]), "+f"(d[10]), "+f"(d[11]), "+f"(d[12]), "+f"(d[13]), "+f"(d[14]), "+f"(d[15]), "+f"(d[16]), "+f"(d[17]), "+f"(d[18]), "+f"(d[19]), "+f"(d[20]), "+f"(d[21]), "+f"(d[22]), "+f"(d[23]), "+f"(d[24]), "+f"(d[25]), "+f"(d[26]), "+f"(d[27]), "+f"(d[28]), "+f"(d[29]), "+f"(d[30]), "+f"(d[31]), "+f"(d[32]), "+f"(d[33]), "+f"(d[34]), "+f"(d[35]), "+f"(d[36]), "+f"(d[37]), "+f"(d[38]), "+f"(d[39]), "+f"(d[40]), "+f"(d[41]), "+f"(d[42]), "+f"(d[43]), "+f"(d[44]), "+f"(d[45]), "+f"(d[46]), "+f"(d[47]), "+f"(d[48]), "+f"(d[49]), "+f"(d[50]), "+f"(d[51]), "+f"(d[52]), "+f"(d[53]), "+f"(d[54]), "+f"(d[55])
    : "r"(a0), "r"(a1), "r"(a2), "r"(a3), "l"(db), "r"(sc), "n"(TB));
}

struct Maps {
  CUtensorMap wm, x, wq, k, v, wo4, wo2, wo1;
  CUtensorMap x1c, x1b, tsa, tsb, y1a, y1b;
  CUtensorMap x1, w1x, w2, ts, ts48, y1, y148, out, out48, w3, w3x, w42;
};
struct Params {
  const __nv_bfloat16 *x, *c, *w_mod, *w1, *w3, *wo, *w2, *w4;
};

constexpr int NSTAGE = 6;
constexpr int STAGE_BYTES = 16384;
constexpr int SM_Q = 0;
constexpr int SM_RING = 131072;
constexpr int SM_MISC = SM_RING + NSTAGE * STAGE_BYTES;
constexpr int SM_GA = SM_MISC;
constexpr int SM_BAR = SM_MISC + 1792;
constexpr int SMEM_BYTES = SM_BAR + 512;
constexpr int B_FULL = 0, B_EMPTY = 6, B_X = 12  , B_X1T = 14, B_TST = 15, B_Y1T = 16  , B_FREEQ = 18, B_FREES1 = 19, B_XI = 20, B_VEC = 21, B_MOD = 22, B_EGF = 24  , B_EGE = 28  , B_ZERO = 32, B_X1T2 = 33, B_TST2 = 34, B_Y1T2 = 35  , B_X1T3 = 37, B_FREEA = 38, B_FREEB = 39;
constexpr int S1_X1T = 0, S1_TST = 57344, S1_VEC = 114688;
constexpr int V_A = 0, V_B = 512, V_C = 1024;
constexpr int V_GB = 1536;
constexpr int V_CALL = 2048, V_SALL = 3840;
constexpr int V_C2F = 5632;
constexpr int V_CONST = 7424;
constexpr int V_GBT = 7456;
constexpr int V_IMG = 7456;
constexpr int V_LIN = 8704;
constexpr int V_QUAD = 10752;
constexpr int V_YST = 11776;
constexpr float QSCALE = 0.0625f * 1.4426950408889634f;

template <int V> struct IC { static constexpr int value = V; };
struct Ring {
  uint32_t full0, empty0, base;
  int s; uint32_t ph;
  __device__ __forceinline__ void advance() { if (++s == NSTAGE) { s = 0; ph ^= 1; } }
  __device__ __forceinline__ uint32_t full() const { return full0 + s * 8; }
  __device__ __forceinline__ uint32_t empty() const { return empty0 + s * 8; }
  __device__ __forceinline__ uint32_t addr() const { return base + s * STAGE_BYTES; }
};

__device__ __forceinline__ void acc8(float (&acc)[8], const uint4& w, float s) {
  acc[0] += s * bf_lo(w.x); acc[1] += s * bf_hi(w.x); acc[2] += s * bf_lo(w.y); acc[3] += s * bf_hi(w.y);
  acc[4] += s * bf_lo(w.z); acc[5] += s * bf_hi(w.z); acc[6] += s * bf_lo(w.w); acc[7] += s * bf_hi(w.w);
}
__device__ __forceinline__ void helper_cta(const Params& p, int hb, unsigned tag, float* sm) {
  const int tid = threadIdx.x - 128;
  PROF(0);
  char* w1s = reinterpret_cast<char*>(sm) + 65536;
#pragma unroll 1
  for (int i = tid; i < DM * 14; i += 256)
    asm volatile("cp.async.cg.shared.global [%0], [%1], 16;" ::"r"(smem_u32(w1s + (i / 14) * 224 + (i % 14) * 16)), "l"(p.w1 + (size_t)(i / 14) * DM + hb * 112 + (i % 14) * 8) : "memory");
  asm volatile("cp.async.commit_group;" ::: "memory");
  if (tid < 28) {
    const int half = tid / 14, ch = tid % 14;
    if (half < (hb < 2 ? 1 : 2)) {
      const int row = (hb == 0) ? 0 : (hb == 1) ? SEQ - 1 : (hb == 2) ? half : SEQ - 2 + half;
      *reinterpret_cast<uint4*>(g_ts + (size_t)(row + 2) * DM + hb * 112 + ch * 8) = make_uint4(0, 0, 0, 0);
    }
  }
  float* sc = sm + 4096;
#pragma unroll 1
  for (int job = 0; job < 2; job++) {
#pragma unroll 1
    for (int i = tid; i < DM; i += 256) { const float cv = __bfloat162float(p.c[i]); sc[i] = job == 0 ? cv * rcp_approx(1.f + ex2(-1.4426950408889634f * cv)) : 1.f; }
    named_bar_sync(5, 256);
    const int grp = tid % 56, part = tid / 56;
    float acc[8];
#pragma unroll
    for (int j = 0; j < 8; j++) acc[j] = 0.f;
    if (part < 4) {
      const __nv_bfloat16* wp = (job == 0 ? p.w_mod + 896 : p.w3) + hb * 448 + grp * 8;
      const int ld = job == 0 ? 6 * DM : FF;
#pragma unroll 1
      for (int k0 = part; k0 < DM; k0 += 32) {
        uint4 w[8];
#pragma unroll
        for (int u = 0; u < 8; u++) w[u] = *reinterpret_cast<const uint4*>(wp + (size_t)(k0 + 4 * u) * ld);
#pragma unroll
        for (int u = 0; u < 8; u++) acc8(acc, w[u], sc[k0 + 4 * u]);
      }
#pragma unroll
      for (int j = 0; j < 8; j++) sm[part * 448 + grp * 8 + j] = acc[j];
    }
    named_bar_sync(5, 256);
#pragma unroll 1
    for (int i = tid; i < 448; i += 256) {
      const float v = (sm[i] + sm[448 + i]) + (sm[896 + i] + sm[1344 + i]);
      if (job == 0) {
        const unsigned long long w = ((unsigned long long)tag << 32) | __float_as_uint(v);
        asm volatile("st.relaxed.gpu.global.b64 [%0], %1;" ::"l"(&g_modt[896 + hb * 448 + i]), "l"(w) : "memory");
      } else {
        const int f = hb * 448 + i;
        const float hi = bf_round(v);
        const __nv_bfloat16 bh = __float2bfloat16(hi), bl = __float2bfloat16(v - hi);
#pragma unroll 1
        for (int rr = 0; rr < 16; rr++) g_w3x[rr * FF + f] = rr < 2 ? bh : rr < 4 ? bl : __float2bfloat16(0.f);
      }
    }
    named_bar_sync(5, 256);
    PROF(1 + job);
  }
  PROF(3);
  float* cs = sm + 4096;
#pragma unroll 1
  for (int i = tid; i < DM; i += 256) { cs[i] = 1.f + mod_wait(4 * DM + i, tag); cs[DM + i] = mod_wait(3 * DM + i, tag); }
  asm volatile("cp.async.wait_all;" ::: "memory");
  named_bar_sync(5, 256);
  {
    const int ch = tid % 14, part = tid / 14;
    float aA[8], aB[8], aC[8];
#pragma unroll
    for (int j = 0; j < 8; j++) { aA[j] = 0.f; aB[j] = 0.f; aC[j] = 0.f; }
    if (part < 16) {
#pragma unroll 1
      for (int k = part; k < DM; k += 16) {
        const uint4 w = *reinterpret_cast<const uint4*>(w1s + k * 224 + ch * 16);
        const float c = cs[k], s = cs[DM + k];
        uint4 o;
        o.x = pack_bf16(bf_lo(w.x) * c, bf_hi(w.x) * c); o.y = pack_bf16(bf_lo(w.y) * c, bf_hi(w.y) * c);
        o.z = pack_bf16(bf_lo(w.z) * c, bf_hi(w.z) * c); o.w = pack_bf16(bf_lo(w.w) * c, bf_hi(w.w) * c);
        acc8(aA, o, 1.f); acc8(aB, w, s); acc8(aC, w, 1.f);
        *reinterpret_cast<uint4*>(g_w1x + ((size_t)hb * DM + k) * 128 + ch * 8) = o;
      }
      float* red = sm + 8192;
#pragma unroll
      for (int j = 0; j < 8; j++) {
        red[(part * 3 + 0) * 112 + ch * 8 + j] = aA[j];
        red[(part * 3 + 1) * 112 + ch * 8 + j] = aB[j];
        red[(part * 3 + 2) * 112 + ch * 8 + j] = aC[j];
      }
    }
#pragma unroll 1
    for (int k = tid; k < DM; k += 256) {
      const float c = cs[k], s = cs[DM + k], c2 = c * c, cv = c * s;
      const float ch_ = bf_round(c), c2h = bf_round(c2), cvh = bf_round(cv);
      uint4* dst = reinterpret_cast<uint4*>(g_w1x + ((size_t)hb * DM + k) * 128 + 112);
      dst[0] = make_uint4(pack_bf16(1.f, ch_), pack_bf16(c - ch_, c2h), pack_bf16(c2 - c2h, cvh), pack_bf16(cv - cvh, 0.f));
      dst[1] = make_uint4(0, 0, 0, 0);
    }
  }
  named_bar_sync(5, 256);
  float* img = g_s1v + hb * 3072;
#pragma unroll 1
  for (int i = tid; i < 384; i += 256) {
    const int v = i >> 7, col = i & 127;
    float s = 0.f;
    if (col < 112) {
#pragma unroll 1
      for (int q = 0; q < 16; q++) s += sm[8192 + (q * 3 + v) * 112 + col];
    }
    img[i] = s;
  }
#pragma unroll 1
  for (int i = tid; i < DM; i += 256) {
    const float c = cs[i], gbv = mod_wait(5 * DM + i, tag);
    img[V_CALL / 4 + i] = c; img[V_SALL / 4 + i] = cs[DM + i];
    img[V_C2F / 4 + ((i >> 4) * 4 + ((i & 7) >> 1)) * 4 + ((i >> 3) & 1) * 2 + (i & 1)] = c * c;
    reinterpret_cast<unsigned short*>(img)[V_GBT / 2 + (((i & 7) >> 1) * 60 + (i >> 3)) * 2 + (i & 1)] = (unsigned short)pack_bf16(0.5f * gbv, 0.f);
    const int lc = i - hb * 112;
    if (lc >= 0 && lc < 112) img[V_GB / 4 + lc] = gbv;
  }
  if (tid < 32) {
    float k0 = 0.f, k1 = 0.f, k2 = 0.f, k3 = 0.f, k4 = 0.f;
#pragma unroll 1
    for (int i = tid; i < DM; i += 32) { const float c = cs[i], s = cs[DM + i]; k0 += c; k1 += c * c; k2 += c * s; k3 += s; k4 += s * s; }
#pragma unroll 1
    for (int o = 16; o > 0; o >>= 1) {
      k0 += __shfl_xor_sync(0xffffffffu, k0, o); k1 += __shfl_xor_sync(0xffffffffu, k1, o); k2 += __shfl_xor_sync(0xffffffffu, k2, o);
      k3 += __shfl_xor_sync(0xffffffffu, k3, o); k4 += __shfl_xor_sync(0xffffffffu, k4, o);
    }
    if (tid == 0) { img[V_CONST / 4] = k0; img[V_CONST / 4 + 1] = k1; img[V_CONST / 4 + 2] = k2; img[V_CONST / 4 + 3] = k3; img[V_CONST / 4 + 4] = k4; }
  }
  named_bar_sync(5, 256);
  PROF(4);
  if (tid == 0) { __threadfence(); flag_arrive(&g_sync.init); }
  __syncwarp();
  if (tid < 32) {
    const char* wo = reinterpret_cast<const char*>(p.wo) + (size_t)hb * (4096 * DM * 2 / NHELP);
    const char* w4 = reinterpret_cast<const char*>(p.w4) + (size_t)hb * (FF * DM * 2 / NHELP);
    const char* w2 = reinterpret_cast<const char*>(p.w2) + (size_t)hb * (DM * DM * 2 / NHELP);
#pragma unroll 1
    for (int i = tid; i < 91; i += 32) {
      const char* a = i < 56 ? wo + i * 16384 : i < 84 ? w4 + (i - 56) * 14336 : w2 + (i - 84) * 14336;
      asm volatile("cp.async.bulk.prefetch.L2.global [%0], %1;" ::"l"(a), "r"(i < 56 ? 16384 : 14336) : "memory");
    }
  }
  __syncwarp();
  PROF(5);
}

__device__ __forceinline__ void mod_group(int grp, unsigned tag, int t, uint32_t wsm, uint32_t csm, uint32_t red  , int barid) {
  float acc[8];
#pragma unroll
  for (int j = 0; j < 8; j++) acc[j] = 0.f;
#pragma unroll
  for (int i = 0; i < 4; i++) {
    const int row = t + 128 * i;
    if (i < 3 || t < 64) {
      uint4 w;
      uint32_t cw;
      asm volatile("ld.shared.v4.u32 {%0,%1,%2,%3}, [%4];" : "=r"(w.x), "=r"(w.y), "=r"(w.z), "=r"(w.w) : "r"(wsm + row * 16));
      asm volatile("ld.shared.u16 %0, [%1];" : "=r"(cw) : "r"(csm + row * 2));
      const float cv = __uint_as_float(cw << 16);
      acc8(acc, w, cv * rcp_approx(1.f + ex2(-1.4426950408889634f * cv)));
    }
  }
#pragma unroll
  for (int o = 1; o < 32; o <<= 1) {
#pragma unroll
    for (int j = 0; j < 8; j++) acc[j] += __shfl_xor_sync(0xffffffffu, acc[j], o);
  }
  if ((t & 31) == 0) {
#pragma unroll
    for (int j = 0; j < 8; j++) sts_f1(red + ((t >> 5) * 8 + j) * 4, acc[j]);
  }
  named_bar_sync(barid, 128);
  if (t < 8) {
    const float s = (lds_f1(red + t * 4) + lds_f1(red + (8 + t) * 4)) + (lds_f1(red + (16 + t) * 4) + lds_f1(red + (24 + t) * 4));
    const unsigned long long w2 = ((unsigned long long)tag << 32) | __float_as_uint(s);
    asm volatile("st.relaxed.gpu.global.b64 [%0], %1;" ::"l"(&g_modt[grp * 8 + t]), "l"(w2) : "memory");
  }
  __syncwarp();
}

#define FULLWAIT() mbar_wait(r.full(), r.ph)
#define PROFW(i)
#define PRED tma_red_2d
#define RELEASE(stage) do { if (elected) mbar_arrive(bar_empty + 8 * (stage)); } while (0)
#define TURN_WAIT() named_bar_sync(3 + cw, 256)
#define TURN_PASS() named_bar_arrive(3 + (cw ^ 1), 256)
#define RING_LOAD(bytes, call) do { mbar_wait(r.empty(), r.ph); mbar_expect_tx(r.full(), bytes); call; r.advance(); } while (0)

__global__ void __launch_bounds__(384, 1) mega_kernel(const __grid_constant__ Maps maps, const Params prm, const int stop_phase) {
  extern __shared__ __align__(1024) uint8_t smem[];
  const uint32_t sb = smem_u32(smem);
  const int tid = threadIdx.x;
  const int wg = __shfl_sync(0xffffffffu, tid >> 7, 0);
  const int bid = blockIdx.x;
  const int tile = bid >> 3, g = bid & 7;
  const uint32_t bars = sb + SM_BAR;
  const uint32_t bar_full = bars + 8 * B_FULL, bar_empty = bars + 8 * B_EMPTY, bar_x = bars + 8 * B_X;
  PROF(9);
  auto load_tag = [] { unsigned e; asm volatile("ld.relaxed.gpu.global.u32 %0, [%1];" : "=r"(e) : "l"(&g_sync.epoch) : "memory"); return e + 1; };

  if (tid == 0) {
    mbar_init(bar_x, 1); mbar_init(bar_x + 8, 1); mbar_init(bars + 8 * B_MOD, 1);
    asm volatile("fence.mbarrier_init.release.cluster;" ::: "memory");
    if (bid < NMAIN) {
      if (bid < 112) {
        mbar_expect_tx(bars + 8 * B_MOD, DM * 16 + DM * 2);
        tma_load_2d(sb + SM_Q + 65536 + 57344, &maps.wm, bid * 8, 0, bars + 8 * B_MOD);
        tma_load_2d(sb + SM_Q + 65536 + 57344 + 224 * 16, &maps.wm, bid * 8, 224, bars + 8 * B_MOD);
        bulk_load_1d(sb + SM_Q + 57344 + 4096, prm.c, DM * 2, bars + 8 * B_MOD);
      }
#pragma unroll 1
      for (int w = 0; w < 2; w++) {
        mbar_expect_tx(bar_x + 8 * w, 7 * 8192);
        tma_load_3d(sb + SM_Q + w * 65536, &maps.x, 0, tile * 128 + w * 64, 0, bar_x + 8 * w);
      }
    }
    for (int i = 0; i < NSTAGE; i++) { mbar_init(bar_full + 8 * i, 1); mbar_init(bar_empty + 8 * i, 8); }
    mbar_init(bars + 8 * B_X1T, 1); mbar_init(bars + 8 * B_TST, 1);
    mbar_init(bars + 8 * B_Y1T, 1); mbar_init(bars + 8 * B_Y1T + 8, 1);
    mbar_init(bars + 8 * B_FREEQ, 2); mbar_init(bars + 8 * B_FREES1, 2); mbar_init(bars + 8 * B_XI, 1); mbar_init(bars + 8 * B_VEC, 1);
    for (int i = 0; i < 8; i++) mbar_init(bars + 8 * (B_EGF + i), 1);
    for (int i = 0; i < 7; i++) mbar_init(bars + 8 * (B_X1T2 + i), 1);
    *reinterpret_cast<uint32_t*>(smem + SM_BAR + 8 * B_ZERO) = 0;
    asm volatile("fence.mbarrier_init.release.cluster;" ::: "memory");
  }
  __syncthreads();

  if (wg == 0) {
    reg_dealloc<24>();
    if (bid >= NMAIN) {
    } else if (tid == 0) {
      Ring r{bar_full, bar_empty, sb + SM_RING, 0, 1};
      const unsigned tag = load_tag();
      const int krow = g * SKV + (SKV - WIN), jg = bid & 3;
      const int seg0 = 0;
      const int nseg = stop_phase >= 3 ? 33 : stop_phase >= 1 ? 25 : 23;
#pragma unroll 1
      for (int sg = seg0; sg < nseg; sg++) {
        const CUtensorMap* m;
        int n, c0 = 0, c1 = 0, d1 = 64, c2 = 0, d2 = 0, bytes = STAGE_BYTES, off2 = 0;
        if (sg < 4) { m = &maps.wq; n = 7; c2 = g * 8 + sg * 2; }
        else if (sg < 20) {
          const int c = ((sg - 4) >> 1) & 3;
          n = 4; c1 = krow + c * 128;
          if (sg & 1) { m = &maps.v; d1 = 32; } else { m = &maps.k; d1 = 0; d2 = 1; }
        }
        else if (sg == 20) { m = &maps.wo4; n = 16; c1 = g * 512; d1 = 32; }
        else if (sg == 21) { m = &maps.wo2; n = 8; c1 = g * 512; c2 = 4; }
        else if (sg == 22) { m = &maps.wo1; n = 4; c1 = g * 512; d1 = 128; c2 = 6; }
        else if (sg == 23) { flag_wait(&g_sync.init, tag * NHELP); fence_async_all(); m = &maps.w1x; n = 7; c1 = jg * DM; }
        else if (sg == 24) { m = &maps.w2; n = 7; c0 = jg * 112; off2 = 8192; }
        else if (sg < 29) {
          c0 = g * 224 + ((sg - 25) >> 1) * 112;
          if (sg & 1) { m = &maps.w3x; n = 1; bytes = 4096; off2 = 2048; } else { m = &maps.w3; n = 7; off2 = 8192; }
        }
        else { m = &maps.w42; n = 4; c1 = g * 224; c2 = sg == 29 ? 6 : ((sg - 30 + g) % 3) * 2; }
#pragma unroll 1
        for (int j = 0; j < n; j++) {
          mbar_wait(r.empty(), r.ph);
          mbar_expect_tx(r.full(), bytes);
          if (off2 == 0) tma_load_3d(r.addr(), m, 0, c1, c2, r.full());
          else { tma_load_2d(r.addr(), m, c0, c1, r.full()); tma_load_2d(r.addr() + off2, m, c0 + 64, c1, r.full()); }
          r.advance();
          c1 += d1; c2 += d2;
        }
      }
    } else if (tid >= 32 && tid < 64) {
      const unsigned tag = load_tag();
      const int ln = tid - 32, ti = bid >> 2;
      if (ln < 2) flag_wait(&g_sync.xi[(tile * 2 + ln) * 8], tag * 7);
#pragma unroll 1
      for (int i = ln; i < DM; i += 32) sts_b16(sb + SM_GA + (((i & 7) >> 1) * 60 + (i >> 3)) * 4 + (i & 1) * 2, pack_bf16(mod_wait(2 * DM + i, tag), 0.f));
      __syncwarp();
      if (ln == 0) mbar_arrive(bars + 8 * B_XI);
      if (stop_phase >= 1) {
        if (ln == 0) {
          flag_wait(&g_sync.init, tag * NHELP);
          mbar_wait(bars + 8 * (B_EGE + 2), 0);
          fence_async_all();
          mbar_expect_tx(bars + 8 * B_VEC, V_IMG);
          bulk_load_1d(sb + S1_VEC, g_s1v + (bid & 3) * 3072, V_IMG, bars + 8 * B_VEC);
          flag_wait(&g_sync.x1a[tile * 8], tag * 16);
          mbar_wait(bars + 8 * B_FREEA, 0);
          fence_async_all();
          mbar_expect_tx(bars + 8 * B_X1T, 4 * 8192);
          tma_load_3d(sb + S1_X1T, &maps.x1b, 0, ti * 64, 0, bars + 8 * B_X1T);
          flag_wait(&g_sync.x1b[tile * 8], tag * 16);
          mbar_wait(bars + 8 * B_FREEB, 0);
          fence_async_all();
          mbar_expect_tx(bars + 8 * B_X1T2, 2 * 8192);
          tma_load_3d(sb + S1_X1T + 4 * 8192, &maps.x1c, 0, ti * 64, 4, bars + 8 * B_X1T2);
          flag_wait(&g_sync.x1[tile * 8], tag * 16);
          mbar_wait(bars + 8 * B_FREEQ, 0);
          fence_async_all();
          mbar_expect_tx(bars + 8 * B_X1T3, 8192 + 960);
          tma_load_2d(sb + S1_X1T + 6 * 8192, &maps.x1, 384, ti * 64, bars + 8 * B_X1T3);
          bulk_load_1d(sb + SM_GA, g_s1v + (bid & 3) * 3072 + V_GBT / 4, 960, bars + 8 * B_X1T3);
        }
        __syncwarp();
        if (stop_phase >= 2) {
          if (ln < 3 && ti + ln >= 1 && ti + ln <= 32) flag_wait(&g_sync.ts[(ti + ln - 1) * 8], tag * 8);
          __syncwarp();
          if (ln == 0) {
            fence_async_all();
            mbar_expect_tx(bars + 8 * B_TST, 3 * 8192);
            tma_load_3d(sb + S1_TST, &maps.tsa, 0, ti * 64 + 2, 0, bars + 8 * B_TST);
            mbar_expect_tx(bars + 8 * B_TST2, 4 * 8192);
            tma_load_3d(sb + S1_TST + 3 * 8192, &maps.tsb, 0, ti * 64 + 2, 3, bars + 8 * B_TST2);
          }
        }
        if (stop_phase >= 3) {
          mbar_wait(bars + 8 * B_FREES1, 0);
          if (ln < 2) {
            flag_wait(&g_sync.y1[(tile * 2 + ln) * 8], tag * 8);
            fence_async_all();
            const uint32_t bar = bars + 8 * (B_Y1T + ln), dst = sb + ln * 65536;
            mbar_expect_tx(bar, 3 * 8192 + 8 * 512);
            tma_load_3d(dst, &maps.y1a, 0, tile * 128 + ln * 64, 0, bar);
            mbar_expect_tx(bars + 8 * (B_Y1T2 + ln), 4 * 8192);
            tma_load_3d(dst + 3 * 8192, &maps.y1b, 0, tile * 128 + ln * 64, 3, bars + 8 * (B_Y1T2 + ln));
#pragma unroll 1
            for (int q = 0; q < 8; q++) bulk_load_1d(dst + 57344 + q * 512, g_ystat + ((size_t)q * SEQ + tile * 128 + ln * 64) * 2, 512, bar);
          }
        }
      }
    } else if ((tid == 64 || tid == 96) && bid < NMAIN) {
      const int w = (tid >> 5) - 2;
      const uint32_t wb = sb + SM_Q + w * 65536;
      const int row = tile * 128 + w * 64;
      const unsigned tag = load_tag();
      mbar_wait(bars + 8 * B_XI, 0);
      fence_async_all();
      if (w == 0) {
        mbar_wait(bars + 8 * B_EGF, 0);
#pragma unroll 1
        for (int q = 0; q < 5; q++) {
          if (q < 4) { const int bx = (q + g) & 3; tma_red_2d(&maps.x1, sb + SM_Q + 32768 + bx * 8192, bx * 64, tile * 128); }
          if (q == 1) mbar_wait(bars + 8 * (B_EGF + 2), 0);
          if (q >= 1) { const int bx = (q - 1 + g) & 3; tma_red_2d(&maps.x1, sb + SM_Q + 65536 + 32768 + bx * 8192, bx * 64, tile * 128 + 64); }
          bulk_commit();
          bulk_wait_read<0>();
          if (q >= 3) mbar_arrive(bars + 8 * (B_EGE + (q - 3) * 2));
        }
        bulk_wait<0>();
        asm volatile("fence.proxy.async.global;\n\tred.release.gpu.global.add.u32 [%0], 2;" ::"l"(&g_sync.x1a[tile * 8]) : "memory");
#pragma unroll 1
        for (int v = 0; v < 2; v++) {
          mbar_wait(bars + 8 * (B_EGF + v * 2), 1);
          tma_red_2d(&maps.x1, sb + SM_Q + v * 65536 + 57344, 384, tile * 128 + v * 64);
          bulk_commit();
        }
        bulk_wait<0>();
        asm volatile("fence.proxy.async.global;\n\tred.release.gpu.global.add.u32 [%0], 2;" ::"l"(&g_sync.x1[tile * 8]) : "memory");
        mbar_arrive(bars + 8 * B_FREEQ);
      } else {
#pragma unroll 1
        for (int v = 0; v < 2; v++) {
          mbar_wait(bars + 8 * (B_EGF + v * 2 + 1), 0);
#pragma unroll 1
          for (int b = 0; b < 2; b++) { const int bx = (b + g) & 1; tma_red_2d(&maps.x1, sb + SM_Q + v * 65536 + 32768 + bx * 8192, 256 + bx * 64, tile * 128 + v * 64); }
          bulk_commit();
        }
        bulk_wait<0>();
        asm volatile("fence.proxy.async.global;\n\tred.release.gpu.global.add.u32 [%0], 2;" ::"l"(&g_sync.x1b[tile * 8]) : "memory");
        mbar_arrive(bars + 8 * B_FREEB);
        mbar_arrive(bars + 8 * B_FREEQ);
      }
      if (stop_phase >= 3) {
        flag_wait(&g_sync.base[(tile * 2 + w) * 8], tag * 8);
        fence_async_all();
#pragma unroll 1
        for (int sq = 0; sq < 4; sq++) {
          mbar_wait(bars + 8 * (B_EGF + w * 2 + (sq & 1)), ((sq & 1) ? 1 : 0) ^ (sq >> 1));
          const int col0 = sq == 0 ? 384 : ((sq - 1 + g) % 3) * 128;
          tma_red_2d(&maps.out, wb + (sq & 1) * 16384, col0, row);
          if (sq > 0) tma_red_2d(&maps.out, wb + (sq & 1) * 16384 + 8192, col0 + 64, row);
          bulk_commit();
          bulk_wait_read<0>();
          mbar_arrive(bars + 8 * (B_EGE + w * 2 + (sq & 1)));
        }
        bulk_wait<0>();
      }
    }
  } else {
    reg_alloc<240>();
    const unsigned tag = load_tag();
    if (bid >= NMAIN) {
      helper_cta(prm, bid - NMAIN, tag, reinterpret_cast<float*>(smem));
    } else {
    PROF(0);
    const int cw = wg - 1;
    const int t = tid & 127, warp = __shfl_sync(0xffffffffu, t >> 5, 0), lane = t & 31;
    const int ct = tid - 128;
    const uint32_t qb = sb + SM_Q + cw * 65536;
    Ring r{bar_full, bar_empty, sb + SM_RING, 0, 0};
    const bool elected = (lane == 0);

    if (bid < 112 && cw == 1) {
      mbar_wait(bars + 8 * B_MOD, 0);
      mod_group(bid, tag, t, sb + SM_Q + 65536 + 57344, sb + SM_Q + 57344 + 4096, sb + SM_Q + 57344 + 5120, 2);
    }

    const int lrow = warp * 16 + ((lane >> 3) & 1) * 8 + (lane & 7);
    const uint32_t laddr = lrow * 128, lx = lrow & 7, lhi = lane >> 4;
    mbar_wait(bar_x + 8 * cw, 0);
    if (t == 0 && g < 7) { tma_store_2d(&maps.x1, qb + g * 8192, g * 64, tile * 128 + cw * 64); bulk_commit(); }
    __syncwarp();
    PROF(1);
    float s0 = 0.f, s1 = 0.f, q0 = 0.f, q1 = 0.f;
#pragma unroll 4
    for (int ks = 0; ks < 28; ks++) {
      uint32_t f0, f1, f2, f3;
      ldsm_x4(qb + (ks >> 2) * 8192 + laddr + ((((ks & 3) * 2 + lhi) ^ lx) << 4), f0, f1, f2, f3);
      float v, w;
      v = bf_lo(f0); w = bf_hi(f0); s0 += v + w; q0 = fmaf(v, v, fmaf(w, w, q0));
      v = bf_lo(f1); w = bf_hi(f1); s1 += v + w; q1 = fmaf(v, v, fmaf(w, w, q1));
      v = bf_lo(f2); w = bf_hi(f2); s0 += v + w; q0 = fmaf(v, v, fmaf(w, w, q0));
      v = bf_lo(f3); w = bf_hi(f3); s1 += v + w; q1 = fmaf(v, v, fmaf(w, w, q1));
    }
    s0 += __shfl_xor_sync(0xffffffffu, s0, 1); s1 += __shfl_xor_sync(0xffffffffu, s1, 1);
    q0 += __shfl_xor_sync(0xffffffffu, q0, 1); q1 += __shfl_xor_sync(0xffffffffu, q1, 1);
    s0 += __shfl_xor_sync(0xffffffffu, s0, 2); s1 += __shfl_xor_sync(0xffffffffu, s1, 2);
    q0 += __shfl_xor_sync(0xffffffffu, q0, 2); q1 += __shfl_xor_sync(0xffffffffu, q1, 2);
    uint32_t rr0w, rr1w, rb0w, rb1w;
    {
      const float m0 = s0 * (1.f / DM), m1 = s1 * (1.f / DM);
      const float r0 = rsqrtf(fmaxf(q0 * (1.f / DM) - m0 * m0, 0.f) + LN_EPS), r1 = rsqrtf(fmaxf(q1 * (1.f / DM) - m1 * m1, 0.f) + LN_EPS);
      rr0w = pack_bf16(r0, r0); rr1w = pack_bf16(r1, r1); rb0w = pack_bf16(-m0 * r0, -m0 * r0); rb1w = pack_bf16(-m1 * r1, -m1 * r1);
    }
    PROF(20);
    const uint32_t modv_s = sb + SM_Q + 57344;
    if (cw == 0) {
      unsigned long long vc[4], vs[4];
      bool ok;
      int guard = 0;
      do {
        ok = true;
#pragma unroll
        for (int i = 0; i < 4; i++) {
          const int col = (i < 3 || t < 64) ? t + 128 * i : t;
          asm volatile("ld.relaxed.gpu.global.b64 %0, [%1];" : "=l"(vc[i]) : "l"(&g_modt[DM + col]) : "memory");
          asm volatile("ld.relaxed.gpu.global.b64 %0, [%1];" : "=l"(vs[i]) : "l"(&g_modt[col]) : "memory");
        }
#pragma unroll
        for (int i = 0; i < 4; i++) ok = ok && (unsigned)(vc[i] >> 32) == tag && (unsigned)(vs[i] >> 32) == tag;
        if (++guard > (1 << 18)) { DBG_FAIL(2); break; }
      } while (!ok);
#pragma unroll
      for (int i = 0; i < 4; i++) {
        const int col = t + 128 * i;
        if (i < 3 || t < 64) {
          const uint32_t p0 = modv_s + ((col >> 4) * 4 + ((col & 7) >> 1)) * 16 + ((col >> 3) & 1) * 8 + (col & 1) * 2;
          sts_b16(p0, pack_bf16(1.f + __uint_as_float((unsigned)vc[i]), 0.f)); sts_b16(p0 + 4, pack_bf16(__uint_as_float((unsigned)vs[i]), 0.f));
        }
      }
      named_bar_arrive(6, 256);
      named_bar_sync(1, 128);
    } else {
      named_bar_sync(6, 256);
    }
    PROF(21);
    const uint32_t rt_zero = lds_u1(bars + 8 * B_ZERO);
    uint32_t a[112];
    auto modulate = [&](auto k0, auto k1) {
#pragma unroll
      for (int ks = decltype(k0)::value; ks < decltype(k1)::value; ks++) {
        ldsm_x4(qb + (ks >> 2) * 8192 + laddr + ((((ks & 3) * 2 + lhi) ^ lx) << 4), a[4 * ks], a[4 * ks + 1], a[4 * ks + 2], a[4 * ks + 3]);
        const uint4 w = ldc_u4(modv_s + rt_zero + (ks * 4 + (lane & 3)) * 16);
        a[4 * ks]     = hfma2_bf16(hfma2_bf16(a[4 * ks], rr0w, rb0w), w.x, w.y);
        a[4 * ks + 1] = hfma2_bf16(hfma2_bf16(a[4 * ks + 1], rr1w, rb1w), w.x, w.y);
        a[4 * ks + 2] = hfma2_bf16(hfma2_bf16(a[4 * ks + 2], rr0w, rb0w), w.z, w.w);
        a[4 * ks + 3] = hfma2_bf16(hfma2_bf16(a[4 * ks + 3], rr1w, rb1w), w.z, w.w);
      }
    };
    modulate(IC<0>{}, IC<16>{});

    PROF(2);
    const int st_row = warp * 16 + ((lane >> 3) & 1) * 8 + (lane & 7);
    const int st_hi = lane >> 4;
    const uint32_t st_off = st_row * 128;
    const int st_x = st_row & 7;

    unsigned starve = 0; (void)starve;
    auto slot_dep = [&](auto ntiles, auto&& issue, uint32_t dep) {
      constexpr int NT = decltype(ntiles)::value;
      FULLWAIT();
      named_bar_sync(3 + cw + (dep & rt_zero), 256);
      wg_fence();
#pragma unroll
      for (int j = 0; j < NT; j++) {
        issue(j, r.addr());
        wg_commit();
        const int prev = r.s == 0 ? NSTAGE - 1 : r.s - 1;
        r.advance();
        if (j == NT - 1) TURN_PASS();
        else { FULLWAIT(); }
        if (j > 0) { wg_wait<1>(); RELEASE(prev); }
      }
      wg_wait<0>();
      RELEASE(r.s == 0 ? NSTAGE - 1 : r.s - 1);
    };
    auto slot = [&](auto ntiles, auto&& issue) { slot_dep(ntiles, issue, 0u); };
    auto run_rt = [&](int nt, auto&& issue, auto&& pre) {
      wg_fence();
#pragma unroll 1
      for (int j = 0; j < nt; j++) {
        pre(j);
        FULLWAIT();
        issue(j, r.addr());
        wg_commit();
        const int prev = r.s == 0 ? NSTAGE - 1 : r.s - 1;
        r.advance();
        if (j > 0) { wg_wait<1>(); RELEASE(prev); }
      }
      wg_wait<0>();
      RELEASE(r.s == 0 ? NSTAGE - 1 : r.s - 1);
    };
    auto slot_rt = [&](int nt, auto&& issue) {
      FULLWAIT();
      TURN_WAIT();
      wg_fence();
#pragma unroll 1
      for (int j = 0; j < nt; j++) {
        issue(j, r.addr());
        wg_commit();
        const int prev = r.s == 0 ? NSTAGE - 1 : r.s - 1;
        r.advance();
        if (j == nt - 1) TURN_PASS();
        else { FULLWAIT(); }
        if (j > 0) { wg_wait<1>(); RELEASE(prev); }
      }
      wg_wait<0>();
      RELEASE(r.s == 0 ? NSTAGE - 1 : r.s - 1);
    };
    if (cw == 1) named_bar_arrive(3, 256);

#pragma unroll 1
    for (int p = 0; p < 4; p++) {
      float acc[64];
      fence_regs_u(a);
      slot(IC<4>{}, [&](int j, uint32_t addr) {
        const uint64_t db = make_desc(addr, 8192, 1024);
#pragma unroll
        for (int ks = 0; ks < 4; ks++) {
          const int i = (j * 4 + ks) * 4;
          wgmma_rs_n128<1>(acc, a[i], a[i + 1], a[i + 2], a[i + 3], db + ks * 128, (j | ks) != 0);
        }
      });
      if (p == 0) modulate(IC<16>{}, IC<28>{});
      fence_regs_u(a);
      slot(IC<3>{}, [&](int j, uint32_t addr) {
        const uint64_t db = make_desc(addr, 8192, 1024);
#pragma unroll
        for (int ks = 0; ks < 4; ks++) {
          const int i = ((j + 4) * 4 + ks) * 4;
          wgmma_rs_n128<1>(acc, a[i], a[i + 1], a[i + 2], a[i + 3], db + ks * 128, 1);
        }
      });
      fence_regs(acc);
      if (p == 0) {
        if (t == 0 && g < 7) { bulk_wait<0>(); flag_arrive_release(&g_sync.xi[(tile * 2 + cw) * 8]); }
        named_bar_sync(1 + cw, 128);
      }
      const uint32_t qdst = qb + (p >> 1) * 32768 + (p & 1) * 16384;
#pragma unroll
      for (int jj = 0; jj < 8; jj++) {
        const int chunk = (jj & 3) * 2 + st_hi;
        stsm_x4(qdst + (jj >> 2) * 8192 + st_off + ((chunk ^ st_x) << 4),
                pack_bf16(acc[8 * jj], acc[8 * jj + 1]), pack_bf16(acc[8 * jj + 2], acc[8 * jj + 3]),
                pack_bf16(acc[8 * jj + 4], acc[8 * jj + 5]), pack_bf16(acc[8 * jj + 6], acc[8 * jj + 7]));
      }
    }
    fence_async_smem();
    named_bar_sync(1 + cw, 128);
    PROF(3); PROFW(24);

    uint32_t o1[64];
#pragma unroll 1
    for (int h = 0; h < 2; h++) {
      float o[128];
      float nb0 = 0.f, nb1 = 0.f, l0 = 0.f, l1 = 0.f;
      const uint32_t qh = qb + h * 32768;
#pragma unroll 1
      for (int c = 0; c < 4; c++) {
        float s[64];
        uint32_t pr[32];
        slot(IC<4>{}, [&](int j, uint32_t addr) {
          const uint64_t da = make_desc(qh + j * 8192, 16, 1024);
          const uint64_t db = make_desc(addr, 16, 1024);
#pragma unroll
          for (int ks = 0; ks < 4; ks++) wgmma_ss_n128<0>(s, da + ks * 2, db + ks * 2, (j | ks) != 0);
        });
        fence_regs(s);
        float a0 = 0.f, a1 = 0.f, a0b = 0.f, a1b = 0.f;
        {
#pragma unroll
          for (int j = 0; j < 16; j++) {
            s[4 * j] = fmaf(s[4 * j], QSCALE, nb0); s[4 * j + 1] = fmaf(s[4 * j + 1], QSCALE, nb0);
            s[4 * j + 2] = fmaf(s[4 * j + 2], QSCALE, nb1); s[4 * j + 3] = fmaf(s[4 * j + 3], QSCALE, nb1);
          }
          int m0 = __float_as_int(s[0]), m1 = __float_as_int(s[1]);
#pragma unroll
          for (int j = 1; j < 32; j += 2) m0 = __vimax3_s32(m0, __float_as_int(s[2 * j]), __float_as_int(s[2 * j + 1]));
#pragma unroll
          for (int j = 2; j < 32; j += 2) m1 = __vimax3_s32(m1, __float_as_int(s[2 * j]), __float_as_int(s[2 * j + 1]));
          if (__any_sync(0xffffffffu, c == 0 || max(m0, m1) > 0x41000000)) {
            float n0 = fmaxf(s[0], s[1]), n1 = fmaxf(s[2], s[3]);
#pragma unroll
            for (int j = 1; j < 16; j++) { n0 = fmaxf(n0, fmaxf(s[4 * j], s[4 * j + 1])); n1 = fmaxf(n1, fmaxf(s[4 * j + 2], s[4 * j + 3])); }
            n0 = fmaxf(n0, __shfl_xor_sync(0xffffffffu, n0, 1)); n1 = fmaxf(n1, __shfl_xor_sync(0xffffffffu, n1, 1));
            n0 = fmaxf(n0, __shfl_xor_sync(0xffffffffu, n0, 2)); n1 = fmaxf(n1, __shfl_xor_sync(0xffffffffu, n1, 2));
            if (c > 0) {
              n0 = fmaxf(n0, 0.f); n1 = fmaxf(n1, 0.f);
              const float sc0 = ex2(-n0), sc1 = ex2(-n1);
              l0 *= sc0; l1 *= sc1;
#pragma unroll
              for (int i = 0; i < 32; i++) { o[4 * i] *= sc0; o[4 * i + 1] *= sc0; o[4 * i + 2] *= sc1; o[4 * i + 3] *= sc1; }
            }
            nb0 -= n0; nb1 -= n1;
#pragma unroll
            for (int j = 0; j < 16; j++) { s[4 * j] -= n0; s[4 * j + 1] -= n0; s[4 * j + 2] -= n1; s[4 * j + 3] -= n1; }
          }
#pragma unroll
          for (int j = 0; j < 16; j++) {
            const float e0 = ex2(s[4 * j]), e1 = ex2(s[4 * j + 1]), e2 = ex2(s[4 * j + 2]), e3 = ex2(s[4 * j + 3]);
            a0 += e0; a0b += e1; a1 += e2; a1b += e3;
            pr[2 * j] = pack_bf16(e0, e1); pr[2 * j + 1] = pack_bf16(e2, e3);
          }
        }
        l0 += a0 + a0b; l1 += a1 + a1b;
        fence_regs(o);
        const uint32_t dep = __float_as_uint(l0) ^ __float_as_uint(l1);
        slot_dep(IC<4>{}, [&](int j, uint32_t addr) {
          const uint64_t db = make_desc(addr, 4096, 1024);
#pragma unroll
          for (int ks = 0; ks < 2; ks++) {
            const int i = (j * 2 + ks) * 4;
            wgmma_rs_n256<1>(o, pr[i], pr[i + 1], pr[i + 2], pr[i + 3], db + ks * 128, (j | ks) != 0 || c != 0);
          }
        }, dep);
        fence_regs(o);
        PROF(4 + h * 5 + c);
      }
      l0 += __shfl_xor_sync(0xffffffffu, l0, 1); l1 += __shfl_xor_sync(0xffffffffu, l1, 1);
      l0 += __shfl_xor_sync(0xffffffffu, l0, 2); l1 += __shfl_xor_sync(0xffffffffu, l1, 2);
      const float i0 = rcp_approx(l0), i1 = rcp_approx(l1);
#pragma unroll
      for (int j = 0; j < 32; j++) {
        o1[2 * j] = pack_bf16(o[4 * j] * i0, o[4 * j + 1] * i0);
        o1[2 * j + 1] = pack_bf16(o[4 * j + 2] * i1, o[4 * j + 3] * i1);
      }
      if (h == 0) {
#pragma unroll
        for (int jj = 0; jj < 16; jj++) {
          const int chunk = (jj & 3) * 2 + st_hi;
          stsm_x4(qb + (jj >> 2) * 8192 + st_off + ((chunk ^ st_x) << 4), o1[4 * jj], o1[4 * jj + 1], o1[4 * jj + 2], o1[4 * jj + 3]);
        }
        mbar_wait(bars + 8 * B_XI, 0);
        fence_async_smem();
        named_bar_sync(1 + cw, 128);
      }
    }

    PROF(14); PROFW(25);
    const uint32_t stg = qb + 32768;
    const uint32_t ga_s = sb + SM_GA + (lane & 3) * 240 + rt_zero;
    {
      float acc[128];
      uint32_t gw[32];
      fence_regs_u(o1);
#pragma unroll 1
      for (int sl = 0; sl < 2; sl++) {
        slot_rt(4, [&](int j, uint32_t addr) {
          const uint64_t db = make_desc(addr, 4096, 1024);
          const uint64_t da = make_desc(qb + (sl * 2 + (j >> 1)) * 8192 + (j & 1) * 64, 16, 1024);
          wgmma_ss_n256<1>(acc, da, db, (sl | j) != 0);
          wgmma_ss_n256<1>(acc, da + 2, db + 128, 1);
        });
      }
#pragma unroll
      for (int sl = 0; sl < 2; sl++) {
        if (sl == 1) {
#pragma unroll
          for (int q = 0; q < 8; q++) { const uint4 v = ldc_u4(ga_s + q * 16); gw[4 * q] = v.x; gw[4 * q + 1] = v.y; gw[4 * q + 2] = v.z; gw[4 * q + 3] = v.w; }
          fence_regs_u(gw);
        }
        slot(IC<4>{}, [&](int j, uint32_t addr) {
          const uint64_t db = make_desc(addr, 4096, 1024);
#pragma unroll
          for (int ks = 0; ks < 2; ks++) { const int i = ((sl * 4 + j) * 2 + ks) * 4; wgmma_rs_n256<1>(acc, o1[i], o1[i + 1], o1[i + 2], o1[i + 3], db + ks * 128, 1); }
        });
      }
      fence_regs(acc);
      {
#pragma unroll
        for (int jj = 0; jj < 16; jj++) {
          const int chunk = (jj & 3) * 2 + st_hi;
          stsm_x4(stg + (jj >> 2) * 8192 + st_off + ((chunk ^ st_x) << 4),
                  hmul2_bf16(pack_bf16(acc[8 * jj], acc[8 * jj + 1]), gw[2 * jj]), hmul2_bf16(pack_bf16(acc[8 * jj + 2], acc[8 * jj + 3]), gw[2 * jj]),
                  hmul2_bf16(pack_bf16(acc[8 * jj + 4], acc[8 * jj + 5]), gw[2 * jj + 1]), hmul2_bf16(pack_bf16(acc[8 * jj + 6], acc[8 * jj + 7]), gw[2 * jj + 1]));
        }
      }
      fence_async_smem();
      named_bar_sync(1 + cw, 128);
      if (t == 0) mbar_arrive(bars + 8 * (B_EGF + cw * 2));
      __syncwarp();
    }
    PROF(15); PROFW(26);
    {
      float acc[64];
      uint32_t gw[16];
      slot_rt(4, [&](int j, uint32_t addr) {
        const uint64_t db = make_desc(addr, 8192, 1024), da = make_desc(qb + j * 8192, 16, 1024);
#pragma unroll
        for (int ks = 0; ks < 4; ks++) wgmma_ss_n128<1>(acc, da + ks * 2, db + ks * 128, (j | ks) != 0);
      });
#pragma unroll
      for (int q = 0; q < 4; q++) { const uint4 v = ldc_u4(ga_s + 128 + q * 16); gw[4 * q] = v.x; gw[4 * q + 1] = v.y; gw[4 * q + 2] = v.z; gw[4 * q + 3] = v.w; }
      fence_regs_u(gw);
      mbar_wait(bars + 8 * (B_EGE + cw * 2), 0);
      slot(IC<4>{}, [&](int j, uint32_t addr) {
        const uint64_t db = make_desc(addr, 8192, 1024);
#pragma unroll
        for (int ks = 0; ks < 4; ks++) { const int i = (j * 4 + ks) * 4; wgmma_rs_n128<1>(acc, o1[i], o1[i + 1], o1[i + 2], o1[i + 3], db + ks * 128, 1); }
      });
      fence_regs(acc);
#pragma unroll
      for (int jj = 0; jj < 8; jj++) {
        stsm_x4(stg + (jj >> 2) * 8192 + st_off + ((((jj & 3) * 2 + st_hi) ^ st_x) << 4),
                hmul2_bf16(pack_bf16(acc[8 * jj], acc[8 * jj + 1]), gw[2 * jj]), hmul2_bf16(pack_bf16(acc[8 * jj + 2], acc[8 * jj + 3]), gw[2 * jj]),
                hmul2_bf16(pack_bf16(acc[8 * jj + 4], acc[8 * jj + 5]), gw[2 * jj + 1]), hmul2_bf16(pack_bf16(acc[8 * jj + 6], acc[8 * jj + 7]), gw[2 * jj + 1]));
      }
      fence_async_smem();
      named_bar_sync(1 + cw, 128);
      if (t == 0) mbar_arrive(bars + 8 * (B_EGF + cw * 2 + 1));
      __syncwarp();
    }
    {
      float acc[32];
      uint32_t gw[8];
      slot_rt(2, [&](int j, uint32_t addr) {
        const uint64_t db = make_desc(addr, 16, 1024);
#pragma unroll
        for (int ks = 0; ks < 8; ks++) wgmma_ss_n64<1>(acc, make_desc(qb + (j * 2 + (ks >> 2)) * 8192, 16, 1024) + (ks & 3) * 2, db + ks * 128, (j | ks) != 0);
      });
      if (cw == 0) {
        named_bar_sync(1, 128);
        if (t == 0) mbar_arrive(bars + 8 * B_FREEA);
        __syncwarp();
      }
#pragma unroll
      for (int q = 0; q < 2; q++) { const uint4 v = ldc_u4(ga_s + 192 + q * 16); gw[4 * q] = v.x; gw[4 * q + 1] = v.y; gw[4 * q + 2] = v.z; gw[4 * q + 3] = v.w; }
      fence_regs_u(gw);
      slot(IC<2>{}, [&](int j, uint32_t addr) {
        const uint64_t db = make_desc(addr, 16, 1024);
#pragma unroll
        for (int ks = 0; ks < 8; ks++) { const int i = (j * 8 + ks) * 4; wgmma_rs_n64<1>(acc, o1[i], o1[i + 1], o1[i + 2], o1[i + 3], db + ks * 128, 1); }
      });
      fence_regs(acc);
#pragma unroll
      for (int jj = 0; jj < 4; jj++) {
        stsm_x4(qb + 57344 + st_off + (((jj * 2 + st_hi) ^ st_x) << 4),
                hmul2_bf16(pack_bf16(acc[8 * jj], acc[8 * jj + 1]), gw[2 * jj]), hmul2_bf16(pack_bf16(acc[8 * jj + 2], acc[8 * jj + 3]), gw[2 * jj]),
                hmul2_bf16(pack_bf16(acc[8 * jj + 4], acc[8 * jj + 5]), gw[2 * jj + 1]), hmul2_bf16(pack_bf16(acc[8 * jj + 6], acc[8 * jj + 7]), gw[2 * jj + 1]));
      }
      fence_async_smem();
      named_bar_sync(1 + cw, 128);
      if (t == 0) mbar_arrive(bars + 8 * (B_EGF + cw * 2));
      __syncwarp();
      PROF(16);
      PROF(17); PROFW(27);
    }
    if (cw == 0) TURN_WAIT();

    if (stop_phase >= 1) {
    const int ti = bid >> 2, jg = bid & 3;
    const uint32_t vec = sb + S1_VEC, x1t = sb + S1_X1T, tst = sb + S1_TST;
    const int q4 = lane & 3;
    const int row0 = warp * 16 + (lane >> 2);
    mbar_wait(bars + 8 * B_VEC, 0);
    const uint32_t vecz = vec + lds_u1(bars + 8 * B_ZERO);
    PROF(22);
    float rm0, rr0, rm1, rr1;
    {
      float acc[32];
      mbar_wait(bars + 8 * B_X1T, 0);
      PROF(23);
      float s2a = 0.f, s2b = 0.f, t2a = 0.f, t2b = 0.f;
      wg_fence();
#pragma unroll 1
      for (int kc = 0; kc < 7; kc++) {
        if (kc == 4) mbar_wait(bars + 8 * B_X1T2, 0);
        if (kc == 6) mbar_wait(bars + 8 * B_X1T3, 0);
        mbar_wait(r.full(), r.ph);
        const uint64_t da = make_desc(x1t + kc * 8192, 16, 1024), db = make_desc(r.addr() + cw * 8192, 16, 1024);
        const int prev = r.s == 0 ? NSTAGE - 1 : r.s - 1;
        r.advance();
#pragma unroll
        for (int i = 0; i < 2; i++) {
          const int ks = kc * 4 + cw * 2 + i;
          uint32_t f0, f1, f2, f3;
          ldsm_x4(x1t + (ks >> 2) * 8192 + laddr + ((((ks & 3) * 2 + lhi) ^ lx) << 4), f0, f1, f2, f3);
          const float4 c2 = lds_f4(vecz + V_C2F + (ks * 4 + q4) * 16);
          wgmma_ss_n64<1>(acc, da + i * 4, db + i * 256, (kc | i) != 0);
          wgmma_ss_n64<1>(acc, da + i * 4 + 2, db + i * 256 + 128, 1);
          if (i == 1) wg_commit();
          float v;
          v = bf_lo(f0); v *= v; s2a += v; t2a = fmaf(v, c2.x, t2a);
          v = bf_hi(f0); v *= v; s2a += v; t2a = fmaf(v, c2.y, t2a);
          v = bf_lo(f1); v *= v; s2b += v; t2b = fmaf(v, c2.x, t2b);
          v = bf_hi(f1); v *= v; s2b += v; t2b = fmaf(v, c2.y, t2b);
          v = bf_lo(f2); v *= v; s2a += v; t2a = fmaf(v, c2.z, t2a);
          v = bf_hi(f2); v *= v; s2a += v; t2a = fmaf(v, c2.w, t2a);
          v = bf_lo(f3); v *= v; s2b += v; t2b = fmaf(v, c2.z, t2b);
          v = bf_hi(f3); v *= v; s2b += v; t2b = fmaf(v, c2.w, t2b);
        }
        if (kc > 0) { wg_wait<1>(); RELEASE(prev); }
      }
      PROFA(8);
      s2a += __shfl_xor_sync(0xffffffffu, s2a, 1); s2b += __shfl_xor_sync(0xffffffffu, s2b, 1);
      t2a += __shfl_xor_sync(0xffffffffu, t2a, 1); t2b += __shfl_xor_sync(0xffffffffu, t2b, 1);
      s2a += __shfl_xor_sync(0xffffffffu, s2a, 2); s2b += __shfl_xor_sync(0xffffffffu, s2b, 2);
      t2a += __shfl_xor_sync(0xffffffffu, t2a, 2); t2b += __shfl_xor_sync(0xffffffffu, t2b, 2);
      if (q4 == 0) { sts_f2(vec + V_QUAD + (cw * 64 + row0) * 8, s2a, t2a); sts_f2(vec + V_QUAD + (cw * 64 + row0 + 8) * 8, s2b, t2b); }
      __syncwarp();
      wg_wait<0>();
      RELEASE(r.s == 0 ? NSTAGE - 1 : r.s - 1);
      fence_regs(acc);
      if (cw == 1) { sts_f2(vec + V_LIN + row0 * 32 + q4 * 8, acc[24], acc[25]); sts_f2(vec + V_LIN + (row0 + 8) * 32 + q4 * 8, acc[26], acc[27]); }
      named_bar_sync(5, 256);
      float al[2], be[2], ga_[2], rh[2];
      {
        const float kc_ = lds_f1(vec + V_CONST), kc2 = lds_f1(vec + V_CONST + 4), kcs = lds_f1(vec + V_CONST + 8), ks_ = lds_f1(vec + V_CONST + 12), ks2 = lds_f1(vec + V_CONST + 16);
#pragma unroll
        for (int e = 0; e < 2; e++) {
          const int row = row0 + 8 * e;
          const float4 la = lds_f4(vec + V_LIN + row * 32), lb = lds_f4(vec + V_LIN + row * 32 + 16);
          const float2 qa = lds_f2(vec + V_QUAD + row * 8), qb2 = lds_f2(vec + V_QUAD + (64 + row) * 8);
          const float S1 = la.x, T1 = la.y + la.z, T3 = la.w + lb.x, T4 = lb.y + lb.z, S2 = qa.x + qb2.x, T2 = qa.y + qb2.y;
          const float m = S1 * (1.f / DM);
          const float rs = rsqrtf(fmaxf(S2 * (1.f / DM) - m * m, 0.f) + LN_EPS);
          const float sh = rs * (T1 - m * kc_) + ks_;
          const float sh2 = rs * rs * (T2 - 2.f * m * T3 + m * m * kc2) + 2.f * rs * (T4 - m * kcs) + ks2;
          const float mh = sh * (1.f / DM);
          rh[e] = rsqrtf(fmaxf(sh2 * (1.f / DM) - mh * mh, 0.f) + LN_EPS);
          al[e] = rh[e] * rs; be[e] = -al[e] * m; ga_[e] = -rh[e] * mh;
          if (e == 0) { rr0 = rs; rm0 = -m * rs; } else { rr1 = rs; rm1 = -m * rs; }
        }
      }
      PROFA(19);
      uint32_t tp[16];
#pragma unroll
      for (int j = 0; j < 8; j++) {
        const uint32_t co = (cw * 64 + j * 8 + q4 * 2) * 4;
        const float2 vA = ldc_f2(vecz + V_A + co), vB = ldc_f2(vecz + V_B + co), vC = ldc_f2(vecz + V_C + co);
        const float p0 = fmaf(al[0], acc[4 * j], fmaf(be[0], vA.x, fmaf(ga_[0], vC.x, rh[0] * vB.x)));
        const float p1 = fmaf(al[0], acc[4 * j + 1], fmaf(be[0], vA.y, fmaf(ga_[0], vC.y, rh[0] * vB.y)));
        const float p2 = fmaf(al[1], acc[4 * j + 2], fmaf(be[1], vA.x, fmaf(ga_[1], vC.x, rh[1] * vB.x)));
        const float p3 = fmaf(al[1], acc[4 * j + 3], fmaf(be[1], vA.y, fmaf(ga_[1], vC.y, rh[1] * vB.y)));
        tp[2 * j] = pack_bf16(gelu2(p0), gelu2(p1));
        tp[2 * j + 1] = pack_bf16(gelu2(p2), gelu2(p3));
      }
      if (cw == 0) {
#pragma unroll
        for (int jj = 0; jj < 4; jj++)
          stsm_x4(tst + st_off + (((jj * 2 + st_hi) ^ st_x) << 4), tp[4 * jj], tp[4 * jj + 1], tp[4 * jj + 2], tp[4 * jj + 3]);
      } else {
#pragma unroll
        for (int jj = 0; jj < 3; jj++)
          stsm_x4(tst + 8192 + st_row * 96 + (jj * 2 + st_hi) * 16, tp[4 * jj], tp[4 * jj + 1], tp[4 * jj + 2], tp[4 * jj + 3]);
      }
      fence_async_smem();
      named_bar_sync(1 + cw, 128);
      PROFA(31);
      if (t == 0) {
        const int shift = 2 + ((jg == 0) ? 1 : (jg == 1) ? -1 : (jg == 2) ? 2 : -2);
        if (cw == 0) tma_store_2d(&maps.ts, tst, jg * 112, ti * 64 + shift);
        else tma_store_2d(&maps.ts48, tst + 8192, jg * 112 + 64, ti * 64 + shift);
        bulk_commit();
        bulk_wait<0>();
        flag_arrive_stored(&g_sync.ts[ti * 8]);
      }
      __syncwarp();
      PROF(24);
    }
    if (stop_phase >= 2) {
      float acc[32];
      float hv[32], gv[16];
      uint32_t xw[16];
#pragma unroll
      for (int j = 0; j < 8; j++) {
        const int lc = cw * 64 + j * 8;
        const int gc = jg * 112 + lc;
        const uint32_t xa = x1t + (vecz - vec) + (gc >> 6) * 8192 + q4 * 4 + row0 * 128 + ((((gc & 63) >> 3) ^ (row0 & 7)) << 4);
        uint32_t x0, x1w;
        asm volatile("ld.shared.u32 %0, [%1];" : "=r"(x0) : "r"(xa)); asm volatile("ld.shared.u32 %0, [%1];" : "=r"(x1w) : "r"(xa + 1024));
        xw[2 * j] = x0; xw[2 * j + 1] = x1w;
        const float2 cv = ldc_f2(vecz + V_CALL + (gc + q4 * 2) * 4), sv = ldc_f2(vecz + V_SALL + (gc + q4 * 2) * 4), g2 = ldc_f2(vecz + V_GB + (lc + q4 * 2) * 4);
        gv[2 * j] = g2.x; gv[2 * j + 1] = g2.y;
        hv[4 * j] = fmaf(fmaf(bf_lo(x0), rr0, rm0), cv.x, sv.x); hv[4 * j + 1] = fmaf(fmaf(bf_hi(x0), rr0, rm0), cv.y, sv.y);
        hv[4 * j + 2] = fmaf(fmaf(bf_lo(x1w), rr1, rm1), cv.x, sv.x); hv[4 * j + 3] = fmaf(fmaf(bf_hi(x1w), rr1, rm1), cv.y, sv.y);
      }
      fence_regs(hv);
      mbar_wait(bars + 8 * B_TST, 0);
      PROF(25);
      wg_fence();
#pragma unroll 1
      for (int kc = 0; kc < 7; kc++) {
        if (kc == 3) mbar_wait(bars + 8 * B_TST2, 0);
        mbar_wait(r.full(), r.ph);
        const uint64_t da = make_desc(tst + kc * 8192, 16, 1024), db = make_desc(r.addr() + cw * 8192, 16, 1024);
#pragma unroll
        for (int ks = 0; ks < 4; ks++) wgmma_ss_n64<1>(acc, da + ks * 2, db + ks * 128, (kc | ks) != 0);
        wg_commit();
        const int prev = r.s == 0 ? NSTAGE - 1 : r.s - 1;
        r.advance();
        if (kc > 0) { wg_wait<1>(); RELEASE(prev); }
      }
      wg_wait<0>();
      RELEASE(r.s == 0 ? NSTAGE - 1 : r.s - 1);
      fence_regs(acc);
      named_bar_sync(5, 256);
      uint32_t yp[16], bp[16];
      float sy0 = 0.f, sq0 = 0.f, sy1 = 0.f, sq1 = 0.f;
#pragma unroll
      for (int j = 0; j < 8; j++) {
        float y00 = fmaf(0.5f, acc[4 * j], hv[4 * j]), y01 = fmaf(0.5f, acc[4 * j + 1], hv[4 * j + 1]);
        float y10 = fmaf(0.5f, acc[4 * j + 2], hv[4 * j + 2]), y11 = fmaf(0.5f, acc[4 * j + 3], hv[4 * j + 3]);
        if (j >= 6 && cw == 1) { y00 = 0.f; y01 = 0.f; y10 = 0.f; y11 = 0.f; }
        sy0 += y00 + y01; sq0 = fmaf(y00, y00, fmaf(y01, y01, sq0));
        sy1 += y10 + y11; sq1 = fmaf(y10, y10, fmaf(y11, y11, sq1));
        yp[2 * j] = pack_bf16(y00, y01); yp[2 * j + 1] = pack_bf16(y10, y11);
        bp[2 * j] = pack_bf16(fmaf(gv[2 * j], y00, bf_lo(xw[2 * j])), fmaf(gv[2 * j + 1], y01, bf_hi(xw[2 * j])));
        bp[2 * j + 1] = pack_bf16(fmaf(gv[2 * j], y10, bf_lo(xw[2 * j + 1])), fmaf(gv[2 * j + 1], y11, bf_hi(xw[2 * j + 1])));
      }
      sy0 += __shfl_xor_sync(0xffffffffu, sy0, 1); sq0 += __shfl_xor_sync(0xffffffffu, sq0, 1);
      sy1 += __shfl_xor_sync(0xffffffffu, sy1, 1); sq1 += __shfl_xor_sync(0xffffffffu, sq1, 1);
      sy0 += __shfl_xor_sync(0xffffffffu, sy0, 2); sq0 += __shfl_xor_sync(0xffffffffu, sq0, 2);
      sy1 += __shfl_xor_sync(0xffffffffu, sy1, 2); sq1 += __shfl_xor_sync(0xffffffffu, sq1, 2);
      if (q4 == 0) { sts_f2(vec + V_YST + (cw * 64 + row0) * 8, sy0, sq0); sts_f2(vec + V_YST + (cw * 64 + row0 + 8) * 8, sy1, sq1); }
      __syncwarp();
      if (cw == 0) {
#pragma unroll
        for (int jj = 0; jj < 4; jj++) {
          stsm_x4(tst + st_off + (((jj * 2 + st_hi) ^ st_x) << 4), yp[4 * jj], yp[4 * jj + 1], yp[4 * jj + 2], yp[4 * jj + 3]);
          stsm_x4(tst + 16384 + st_off + (((jj * 2 + st_hi) ^ st_x) << 4), bp[4 * jj], bp[4 * jj + 1], bp[4 * jj + 2], bp[4 * jj + 3]);
        }
      } else {
#pragma unroll
        for (int jj = 0; jj < 3; jj++) {
          stsm_x4(tst + 8192 + st_row * 96 + (jj * 2 + st_hi) * 16, yp[4 * jj], yp[4 * jj + 1], yp[4 * jj + 2], yp[4 * jj + 3]);
          stsm_x4(tst + 24576 + st_row * 96 + (jj * 2 + st_hi) * 16, bp[4 * jj], bp[4 * jj + 1], bp[4 * jj + 2], bp[4 * jj + 3]);
        }
      }
      fence_async_smem();
      named_bar_sync(1 + cw, 128);
      if (t == 0) {
        if (cw == 0) tma_store_2d(&maps.y1, tst, jg * 112, ti * 64);
        else tma_store_2d(&maps.y148, tst + 8192, jg * 112 + 64, ti * 64);
        bulk_store_1d(g_ystat + ((size_t)(jg * 2 + cw) * SEQ + ti * 64) * 2, vec + V_YST + cw * 512, 512);
        bulk_commit();
        if (cw == 0) tma_store_2d(&maps.out, tst + 16384, jg * 112, ti * 64);
        else tma_store_2d(&maps.out48, tst + 24576, jg * 112 + 64, ti * 64);
        bulk_commit();
        bulk_wait<1>();
        flag_arrive_stored(&g_sync.y1[ti * 8]);
        bulk_wait_read<0>();
      }
      __syncwarp();
      named_bar_sync(5, 256);
      if (t == 0) {
        mbar_arrive(bars + 8 * B_FREES1);
        bulk_wait<0>();
        flag_arrive_release(&g_sync.base[ti * 8]);
      }
      __syncwarp();
      PROF(26);
    }
    if (stop_phase >= 3) {
      if (cw == 1) named_bar_arrive(3, 256);
      uint32_t hp[56];
      {
        mbar_wait(bars + 8 * (B_Y1T + cw), 0);
        PROF(27);
        float rs0, rs1;
        uint32_t e0, e1;
        {
          const uint32_t ys = qb + 57344;
          const float2 u0 = lds_f2(ys + (2 * q4) * 512 + row0 * 8), u1 = lds_f2(ys + (2 * q4 + 1) * 512 + row0 * 8);
          const float2 w0 = lds_f2(ys + (2 * q4) * 512 + (row0 + 8) * 8), w1_ = lds_f2(ys + (2 * q4 + 1) * 512 + (row0 + 8) * 8);
          float a0 = u0.x + u1.x, b0_ = u0.y + u1.y, a1 = w0.x + w1_.x, b1_ = w0.y + w1_.y;
          a0 += __shfl_xor_sync(0xffffffffu, a0, 1); b0_ += __shfl_xor_sync(0xffffffffu, b0_, 1);
          a1 += __shfl_xor_sync(0xffffffffu, a1, 1); b1_ += __shfl_xor_sync(0xffffffffu, b1_, 1);
          a0 += __shfl_xor_sync(0xffffffffu, a0, 2); b0_ += __shfl_xor_sync(0xffffffffu, b0_, 2);
          a1 += __shfl_xor_sync(0xffffffffu, a1, 2); b1_ += __shfl_xor_sync(0xffffffffu, b1_, 2);
          const float mn0 = a0 * (1.f / DM), mn1 = a1 * (1.f / DM);
          rs0 = rsqrtf(fmaxf(b0_ * (1.f / DM) - mn0 * mn0, 0.f) + LN_EPS);
          rs1 = rsqrtf(fmaxf(b1_ * (1.f / DM) - mn1 * mn1, 0.f) + LN_EPS);
          const float h0 = bf_round(mn0), h1 = bf_round(mn1);
          e0 = q4 < 2 ? pack_bf16(-h0, h0 - mn0) : 0u; e1 = q4 < 2 ? pack_bf16(-h1, h1 - mn1) : 0u;
        }
        uint32_t ya[112];
#pragma unroll
        for (int ks = 0; ks < 12; ks++)
          ldsm_x4(qb + (ks >> 2) * 8192 + laddr + ((((ks & 3) * 2 + lhi) ^ lx) << 4), ya[4 * ks], ya[4 * ks + 1], ya[4 * ks + 2], ya[4 * ks + 3]);
        fence_regs_u(ya);
        PROFC(4);
#pragma unroll 1
        for (int hf = 0; hf < 2; hf++) {
          float acc[56];
          slot(IC<4>{}, [&](int j, uint32_t addr) {
            if (j == 0) { wgmma_rs_n112<1>(acc, e0, e1, 0u, 0u, make_desc(addr, 2048, 1024), 0); }
            else {
              const uint64_t db = make_desc(addr, 8192, 1024);
#pragma unroll
              for (int ks = 0; ks < 4; ks++) { const int i = ((j - 1) * 4 + ks) * 4; wgmma_rs_n112<1>(acc, ya[i], ya[i + 1], ya[i + 2], ya[i + 3], db + ks * 128, 1); }
            }
          });
          if (hf == 0) {
            PROFC(5);
            mbar_wait(bars + 8 * (B_Y1T2 + cw), 0);
#pragma unroll
            for (int ks = 12; ks < 28; ks++)
              ldsm_x4(qb + (ks >> 2) * 8192 + laddr + ((((ks & 3) * 2 + lhi) ^ lx) << 4), ya[4 * ks], ya[4 * ks + 1], ya[4 * ks + 2], ya[4 * ks + 3]);
          }
          fence_regs_u(ya);
          slot(IC<4>{}, [&](int j, uint32_t addr) {
            const uint64_t db = make_desc(addr, 8192, 1024);
#pragma unroll
            for (int ks = 0; ks < 4; ks++) { const int i = ((j + 3) * 4 + ks) * 4; wgmma_rs_n112<1>(acc, ya[i], ya[i + 1], ya[i + 2], ya[i + 3], db + ks * 128, 1); }
          });
          fence_regs(acc);
          if (hf == 0) PROFC(6); else PROFC(7);
#pragma unroll
          for (int j = 0; j < 7; j++) {
            const uint32_t v0 = pack_bf16(gelu2(acc[8 * j] * rs0), gelu2(acc[8 * j + 1] * rs0)), v1 = pack_bf16(gelu2(acc[8 * j + 2] * rs1), gelu2(acc[8 * j + 3] * rs1));
            const uint32_t v2 = pack_bf16(gelu2(acc[8 * j + 4] * rs0), gelu2(acc[8 * j + 5] * rs0)), v3 = pack_bf16(gelu2(acc[8 * j + 6] * rs1), gelu2(acc[8 * j + 7] * rs1));
            asm volatile("st.shared.v4.u32 [%0], {%1, %2, %3, %4};" ::"r"(qb + 32768 + ((hf * 7 + j) * 128 + t) * 16), "r"(v0), "r"(v1), "r"(v2), "r"(v3) : "memory");
          }
          if (hf == 0) PROF(28);
        }
#pragma unroll
        for (int j = 0; j < 14; j++)
          asm volatile("ld.shared.v4.u32 {%0,%1,%2,%3}, [%4];" : "=r"(hp[4 * j]), "=r"(hp[4 * j + 1]), "=r"(hp[4 * j + 2]), "=r"(hp[4 * j + 3]) : "r"(qb + 32768 + (j * 128 + t) * 16) : "memory");
      }
      PROF(29);
      {
        const uint32_t gb_s = sb + SM_GA + q4 * 240 + rt_zero;
        auto g4_prologue = [&](auto& gw, int nq, int p, int sq) {
#pragma unroll
          for (int q = 0; q < 4; q++) if (q < nq) { const uint4 v = ldc_u4(gb_s + p * 64 + q * 16); gw[4 * q] = v.x; gw[4 * q + 1] = v.y; gw[4 * q + 2] = v.z; gw[4 * q + 3] = v.w; }
          fence_regs_u(gw);
          if (sq >= 2) mbar_wait(bars + 8 * (B_EGE + cw * 2 + (sq & 1)), (sq & 1) ? 0 : 1);
        };
        auto g4_epilogue = [&](auto ngrp, auto& acc, auto& gw, int p, int sq) {
          constexpr int NG = decltype(ngrp)::value;
          const uint32_t stg = qb + (sq & 1) * 16384;
#pragma unroll
          for (int jj = 0; jj < NG; jj++) {
            stsm_x4(stg + (jj >> 2) * 8192 + st_off + ((((jj & 3) * 2 + st_hi) ^ st_x) << 4),
                    hmul2_bf16(pack_bf16(acc[8 * jj], acc[8 * jj + 1]), gw[2 * jj]), hmul2_bf16(pack_bf16(acc[8 * jj + 2], acc[8 * jj + 3]), gw[2 * jj]),
                    hmul2_bf16(pack_bf16(acc[8 * jj + 4], acc[8 * jj + 5]), gw[2 * jj + 1]), hmul2_bf16(pack_bf16(acc[8 * jj + 6], acc[8 * jj + 7]), gw[2 * jj + 1]));
          }
          fence_async_smem();
          named_bar_sync(1 + cw, 128);
          if (t == 0) mbar_arrive(bars + 8 * (B_EGF + cw * 2 + (sq & 1)));
          __syncwarp();
        };
#pragma unroll 1
        for (int sq = 0; sq < 4; sq++) {
          float acc[64];
          uint32_t gw[16];
          const int cp = sq == 0 ? 3 : (sq - 1 + g) % 3;
          g4_prologue(gw, 4, cp, sq);
          fence_regs_u(hp);
          slot_dep(IC<4>{}, [&](int j, uint32_t addr) {
            const uint64_t db = make_desc(addr, 8192, 1024);
#pragma unroll
            for (int ks = 0; ks < 4; ks++) if (j * 4 + ks < 14) { const int i = (j * 4 + ks) * 4; wgmma_rs_n128<1>(acc, hp[i], hp[i + 1], hp[i + 2], hp[i + 3], db + ks * 128, (j | ks) != 0); }
          }, 0u);
          fence_regs(acc);
          g4_epilogue(IC<8>{}, acc, gw, cp, sq);
          if (sq == 0) PROFB(18);
        }
        PROFB(19);
        PROF(30);
      }
      if (cw == 0) TURN_WAIT();
    }
    }

    if (t == 0) {
      unsigned d;
      asm volatile("atom.relaxed.gpu.global.add.u32 %0, [%1], 1;" : "=r"(d) : "l"(&g_sync.done) : "memory");
      PROFA(13);
      if (d + 1 == tag * (2 * NMAIN)) asm volatile("st.relaxed.gpu.global.u32 [%0], %1;" ::"l"(&g_sync.epoch), "r"(tag) : "memory");
    }
    }
  }
}

typedef CUresult (*PFN_encodeTiled)(CUtensorMap*, CUtensorMapDataType, cuuint32_t, void*, const cuuint64_t*, const cuuint64_t*,
                                    const cuuint32_t*, const cuuint32_t*, CUtensorMapInterleave, CUtensorMapSwizzle,
                                    CUtensorMapL2promotion, CUtensorMapFloatOOBfill);
PFN_encodeTiled get_encode() {
  static PFN_encodeTiled fn = nullptr;
  if (!fn) {
    void* p = nullptr;
    cudaDriverEntryPointQueryResult qr;
    cudaGetDriverEntryPoint("cuTensorMapEncodeTiled", &p, cudaEnableDefault, &qr);
    fn = (PFN_encodeTiled)p;
  }
  return fn;
}
CUtensorMap make_map(const void* ptr, int rank, const uint64_t* dims, const uint64_t* strides, const uint32_t* box, bool swz = true) {
  CUtensorMap m;
  uint32_t es[5] = {1, 1, 1, 1, 1};
  get_encode()(&m, CU_TENSOR_MAP_DATA_TYPE_BFLOAT16, rank, const_cast<void*>(ptr), (const cuuint64_t*)dims, (const cuuint64_t*)strides,
               box, es, CU_TENSOR_MAP_INTERLEAVE_NONE, swz ? CU_TENSOR_MAP_SWIZZLE_128B : CU_TENSOR_MAP_SWIZZLE_NONE,
               CU_TENSOR_MAP_L2_PROMOTION_L2_256B, CU_TENSOR_MAP_FLOAT_OOB_FILL_NONE);
  return m;
}
CUtensorMap map2d(const void* p, uint64_t cols, uint64_t rows, uint32_t bc, uint32_t br, bool swz = true) {
  uint64_t d[2] = {cols, rows}, s[1] = {cols * 2};
  uint32_t b[2] = {bc, br};
  return make_map(p, 2, d, s, b, swz);
}
CUtensorMap map3d(const void* p, uint64_t cols, uint64_t rows, uint32_t br, uint32_t bo) {
  uint64_t d[3] = {64, rows, cols / 64}, s[2] = {cols * 2, 128};
  uint32_t b[3] = {64, br, bo};
  return make_map(p, 3, d, s, b);
}
template <typename T> void* sym_addr(T& s) { void* p = nullptr; cudaGetSymbolAddress(&p, s); return p; }

}

#define STOP_PHASE 3

extern "C" void kernel_launch(void* const* d_in, const int* in_sizes, int n_in, void* d_out, int out_size) {
  const __nv_bfloat16* x = (const __nv_bfloat16*)d_in[0];
  const __nv_bfloat16* kc = (const __nv_bfloat16*)d_in[1];
  const __nv_bfloat16* vc = (const __nv_bfloat16*)d_in[2];
  const __nv_bfloat16* wq = (const __nv_bfloat16*)d_in[3];
  const __nv_bfloat16* wo = (const __nv_bfloat16*)d_in[4];
  const __nv_bfloat16* w1 = (const __nv_bfloat16*)d_in[6];
  const __nv_bfloat16* w2 = (const __nv_bfloat16*)d_in[7];
  const __nv_bfloat16* w3 = (const __nv_bfloat16*)d_in[8];
  const __nv_bfloat16* w4 = (const __nv_bfloat16*)d_in[9];
  const __nv_bfloat16* cvec = (const __nv_bfloat16*)d_in[10];
  const __nv_bfloat16* w_mod = (const __nv_bfloat16*)d_in[11];
  cudaStream_t st = cudaStreamPerThread;

  Maps m;
  m.wm = map2d(w_mod, 6 * DM, DM, 8, 224, false);
  m.x = map3d(x, DM, SEQ, 64, 7);
  m.x1c = map3d(sym_addr(g_x1), DM, SEQ, 64, 2); m.x1b = map3d(sym_addr(g_x1), DM, SEQ, 64, 4);
  m.tsa = map3d(sym_addr(g_ts), DM, SEQ + 4, 64, 3); m.tsb = map3d(sym_addr(g_ts), DM, SEQ + 4, 64, 4);
  m.y1a = map3d(sym_addr(g_y1), DM, SEQ, 64, 3); m.y1b = map3d(sym_addr(g_y1), DM, SEQ, 64, 4);
  m.wq = map3d(wq, 4096, DM, 64, 2);
  m.k = map3d(kc, DH, HKV * SKV, 128, 1);
  m.v = map3d(vc, DH, HKV * SKV, 32, 4);
  m.wo4 = map3d(wo, DM, 4096, 32, 4);
  m.wo2 = map3d(wo, DM, 4096, 64, 2);
  m.wo1 = map3d(wo, DM, 4096, 128, 1);
  m.x1 = map2d(sym_addr(g_x1), DM, SEQ, 64, 64);
  m.w1x = map3d(sym_addr(g_w1x), 128, 4 * DM, 64, 2);
  m.w2 = map2d(w2, DM, DM, 64, 64);
  m.ts = map2d(sym_addr(g_ts), DM, SEQ + 4, 64, 64);
  m.ts48 = map2d(sym_addr(g_ts), DM, SEQ + 4, 48, 64, false);
  m.y1 = map2d(sym_addr(g_y1), DM, SEQ, 64, 64);
  m.y148 = map2d(sym_addr(g_y1), DM, SEQ, 48, 64, false);
  m.out = map2d(d_out, DM, SEQ, 64, 64);
  m.out48 = map2d(d_out, DM, SEQ, 48, 64, false);
  m.w3 = map2d(w3, FF, DM, 64, 64);
  m.w3x = map2d(sym_addr(g_w3x), FF, 16, 64, 16);
  m.w42 = map3d(w4, DM, FF, 64, 2);
  Params prm{x, cvec, w_mod, w1, w3, wo, w2, w4};
  cudaFuncSetAttribute(mega_kernel, cudaFuncAttributeMaxDynamicSharedMemorySize, SMEM_BYTES);
  mega_kernel<<<NCTA, 384, SMEM_BYTES, st>>>(m, prm, STOP_PHASE);
}
```
